```python
import torch

def _softmax(x, axis=-1):
    return torch.softmax(x, dim=axis)
def _gelu(x):
    return torch.nn.functional.gelu(x, approximate="tanh")
def _silu(x):
    return torch.nn.functional.silu(x)
def _sigmoid(x):
    return torch.sigmoid(x)
def _layernorm(x, axis=-1, eps=1e-5):
    m = x.mean(dim=axis, keepdim=True)
    v = x.var(dim=axis, keepdim=True, unbiased=False)
    return (x - m) / torch.sqrt(v + eps)
def _scatter_add(tgt, idx, src, axis=0):
    return tgt.clone().index_add_(axis, idx, src)
def _segment_sum(src, seg, n):
    out = torch.zeros((n,) + src.shape[1:], dtype=src.dtype)
    return out.index_add_(0, seg, src)
def _pad(x, pw):
    flat = tuple(v for pair in reversed(pw) for v in pair)
    return torch.nn.functional.pad(x, flat)

kernel_name = 'concat_heads__sliding_block_cached__sliding_block_cached__decode'

def setup_inputs():

    _w = (lambda a: (lambda t: t.to(torch.bfloat16) if t.is_floating_point() else t)(torch.as_tensor(a)))
    def _A_setup():
        B, Sq, D = 2, 1, 512
        Hq, Hkv, Sk, Dh = 32, 32, 8192, 128
        assert Hq % Hkv == 0, (Hq, Hkv)
        return {
            "x": _w((lambda *s: torch.randn(*s, dtype=torch.bfloat16) * 0.8)(B, Sq, D)),
            "k_cache": _w((lambda *s: torch.randn(*s, dtype=torch.bfloat16) * 1.6)(B, Hkv, Sk, Dh)),
            "v_cache": _w((lambda *s: torch.randn(*s, dtype=torch.bfloat16) * 0.2)(B, Hkv, Sk, Dh)),
            "wq": _w((lambda *s: torch.randn(*s, dtype=torch.bfloat16) * 1.6)(D, Hq * Dh) * (D ** -0.5)),
            "wo": _w((lambda *s: torch.randn(*s, dtype=torch.bfloat16) * 0.2)(Hq * Dh, D) * ((Hq * Dh) ** -0.5)),
        }
    _A_in = _A_setup()

    def _B_setup():
        B, Sq, D = 2, 1, 512
        Hq, Hkv, Sk, Dh = 32, 32, 8192, 128
        assert Hq % Hkv == 0, (Hq, Hkv)
        return {
            "x": _w((lambda *s: torch.randn(*s, dtype=torch.bfloat16) * 0.8)(B, Sq, D)),
            "k_cache": _w((lambda *s: torch.randn(*s, dtype=torch.bfloat16) * 1.6)(B, Hkv, Sk, Dh)),
            "v_cache": _w((lambda *s: torch.randn(*s, dtype=torch.bfloat16) * 0.2)(B, Hkv, Sk, Dh)),
            "wq": _w((lambda *s: torch.randn(*s, dtype=torch.bfloat16) * 1.6)(D, Hq * Dh) * (D ** -0.5)),
            "wo": _w((lambda *s: torch.randn(*s, dtype=torch.bfloat16) * 0.2)(Hq * Dh, D) * ((Hq * Dh) ** -0.5)),
        }
    _B_in = _B_setup()

    return {
        "A_x": _A_in["x"],
        "A_k_cache": _A_in["k_cache"],
        "A_v_cache": _A_in["v_cache"],
        "A_wq": _A_in["wq"],
        "A_wo": _A_in["wo"],
        "B_x": _B_in["x"],
        "B_k_cache": _B_in["k_cache"],
        "B_v_cache": _B_in["v_cache"],
        "B_wq": _B_in["wq"],
        "B_wo": _B_in["wo"],
    }

def reference(A_x, A_k_cache, A_v_cache, A_wq, A_wo, B_x, B_k_cache, B_v_cache, B_wq, B_wo):
    def _A_ref(x, k_cache, v_cache, wq, wo):
        B, Sq, D = x.shape
        Hq, Dh = 32, 128
        Hkv, Sk = k_cache.shape[1], k_cache.shape[2]
        W = min(4096, max(256, Sk // 4))
        rep = Hq // Hkv
        q = (lambda x, *d: x.permute(*d))((x @ wq).reshape(B, Sq, Hq, Dh), 0, 2, 1, 3)
        k = (lambda x, n, axis: torch.repeat_interleave(x, n, dim=axis))(k_cache[:, :, Sk - W:, :], rep, axis=1)
        v = (lambda x, n, axis: torch.repeat_interleave(x, n, dim=axis))(v_cache[:, :, Sk - W:, :], rep, axis=1)
        scores = torch.einsum("bhqd,bhkd->bhqk", q, k) * (Dh ** -0.5)
        p = _softmax(scores, axis=-1)
        o = torch.einsum("bhqk,bhkd->bhqd", p, v)
        return (lambda x, *d: x.permute(*d))(o, 0, 2, 1, 3).reshape(B, Sq, Hq * Dh) @ wo

    def _B_ref(x, k_cache, v_cache, wq, wo):
        B, Sq, D = x.shape
        Hq, Dh = 32, 128
        Hkv, Sk = k_cache.shape[1], k_cache.shape[2]
        W = min(4096, max(256, Sk // 4))
        rep = Hq // Hkv
        q = (lambda x, *d: x.permute(*d))((x @ wq).reshape(B, Sq, Hq, Dh), 0, 2, 1, 3)
        k = (lambda x, n, axis: torch.repeat_interleave(x, n, dim=axis))(k_cache[:, :, Sk - W:, :], rep, axis=1)
        v = (lambda x, n, axis: torch.repeat_interleave(x, n, dim=axis))(v_cache[:, :, Sk - W:, :], rep, axis=1)
        scores = torch.einsum("bhqd,bhkd->bhqk", q, k) * (Dh ** -0.5)
        p = _softmax(scores, axis=-1)
        o = torch.einsum("bhqk,bhkd->bhqd", p, v)
        return (lambda x, *d: x.permute(*d))(o, 0, 2, 1, 3).reshape(B, Sq, Hq * Dh) @ wo

    a = _A_ref(A_x, A_k_cache, A_v_cache, A_wq, A_wo)
    b = _B_ref(B_x, B_k_cache, B_v_cache, B_wq, B_wo)
    return torch.concatenate([a, b], axis=-1)
```

```cpp
#include <cuda_runtime.h>
#include <cuda_bf16.h>
#include <stdint.h>

namespace {

constexpr int kSk = 8192, kW = 2048, kDh = 128, kH = 32, kD = 512;
constexpr int TILE_BYTES = 16384;
#define CFG_NS 12
#define CFG_NF 5
constexpr int NS = CFG_NS;
constexpr int NF = CFG_NF;
static_assert(NS % 2 == 0 && NF <= NS, "ring config");
constexpr int K_TILES = 32, V_TILES = 32, WO_TILES = 4;
constexpr int N_TILES = K_TILES + V_TILES + WO_TILES;
constexpr int NCW = 8;
constexpr int THREADS = (NCW + 1) * 32;
constexpr unsigned SPIN_LIMIT = 1u << 18;

constexpr int SM_RING = 0;
constexpr int SM_SCORES = SM_RING + NS * TILE_BYTES;
constexpr int SM_P = SM_SCORES + kW * 4;
constexpr int SM_RED = SM_P + kW * 2;
constexpr int SM_QRECV = SM_RED + NCW * 2 * 128 * 4;
constexpr int SM_QBF = SM_QRECV + 128 * 4;
constexpr int SM_OBF = SM_QBF + 128 * 2;
constexpr int SM_WRED = SM_OBF + 2 * 64 * 2;
constexpr int SM_BAR = SM_WRED + 16 * 4;
constexpr int SM_TOTAL = SM_BAR + (2 * NS + 2) * 8;

struct Params {
    const __nv_bfloat16* x[2];
    const __nv_bfloat16* k[2];
    const __nv_bfloat16* v[2];
    const __nv_bfloat16* wq[2];
    const __nv_bfloat16* wo[2];
    __nv_bfloat16* out;
    int fused;
};

__device__ uint4 g_part[128 * 64 * 4];

#define TS(i) do { } while (0)

__device__ __forceinline__ uint32_t smem_u32(const void* p) { return (uint32_t)__cvta_generic_to_shared(p); }
__device__ __forceinline__ void mbar_init(uint32_t bar, uint32_t cnt) {
    asm volatile("mbarrier.init.shared::cta.b64 [%0], %1;" :: "r"(bar), "r"(cnt) : "memory");
}
__device__ __forceinline__ void mbar_expect_tx(uint32_t bar, uint32_t bytes) {
    asm volatile("mbarrier.arrive.expect_tx.shared::cta.b64 _, [%0], %1;" :: "r"(bar), "r"(bytes) : "memory");
}
__device__ __forceinline__ void mbar_arrive(uint32_t bar) {
    asm volatile("mbarrier.arrive.shared::cta.b64 _, [%0];" :: "r"(bar) : "memory");
}
__device__ __forceinline__ bool mbar_try(uint32_t bar, uint32_t parity) {
    uint32_t ok;
    asm volatile("{\n.reg .pred p;\nmbarrier.try_wait.parity.shared::cta.b64 p, [%1], %2;\nselp.u32 %0, 1, 0, p;\n}"
                 : "=r"(ok) : "r"(bar), "r"(parity) : "memory");
    return ok != 0;
}
__device__ __forceinline__ bool mbar_try_cluster(uint32_t bar, uint32_t parity) {
    uint32_t ok;
    asm volatile("{\n.reg .pred p;\nmbarrier.try_wait.parity.acquire.cluster.shared::cta.b64 p, [%1], %2;\nselp.u32 %0, 1, 0, p;\n}"
                 : "=r"(ok) : "r"(bar), "r"(parity) : "memory");
    return ok != 0;
}
#define SPIN_FAIL(code) __trap()
__device__ __forceinline__ void mbar_wait1(uint32_t bar, uint32_t parity, int code = 0) {
    unsigned n = 0;
    bool ok;
    do { ok = mbar_try(bar, parity); } while (!ok && ++n < SPIN_LIMIT);
    if (!ok) SPIN_FAIL(code);
}
__device__ __forceinline__ void mbar_wait(uint32_t bar, uint32_t parity, int code = 0) {
    unsigned n = 0;
    bool ok;
    do { ok = mbar_try(bar, parity); } while (!ok && ++n < SPIN_LIMIT);
    __syncwarp();
    if (!ok) SPIN_FAIL(code);
    __syncwarp();
}
__device__ __forceinline__ void mbar_wait_cluster(uint32_t bar, uint32_t parity, int code = 0) {
    unsigned n = 0;
    bool ok;
    do { ok = mbar_try_cluster(bar, parity); } while (!ok && ++n < SPIN_LIMIT);
    __syncwarp();
    if (!ok) SPIN_FAIL(code);
    __syncwarp();
}
__device__ __forceinline__ void bulk_load(uint32_t dst, const void* src, uint32_t bytes, uint32_t bar, uint64_t pol) {
    asm volatile("cp.async.bulk.shared::cluster.global.mbarrier::complete_tx::bytes.L2::cache_hint [%0], [%1], %2, [%3], %4;"
                 :: "r"(dst), "l"(src), "r"(bytes), "r"(bar), "l"(pol) : "memory");
}
__device__ __forceinline__ uint4 ldg_stream(const void* p, uint64_t pol) {
    uint4 v;
    asm volatile("ld.global.nc.L1::no_allocate.L2::cache_hint.v4.u32 {%0,%1,%2,%3}, [%4], %5;"
                 : "=r"(v.x), "=r"(v.y), "=r"(v.z), "=r"(v.w) : "l"(p), "l"(pol));
    return v;
}
__device__ __forceinline__ uint4 lds128(uint32_t a) {
    uint4 v;
    asm volatile("ld.shared.v4.u32 {%0,%1,%2,%3}, [%4];" : "=r"(v.x), "=r"(v.y), "=r"(v.z), "=r"(v.w) : "r"(a));
    return v;
}
__device__ __forceinline__ uint2 lds64(uint32_t a) {
    uint2 v;
    asm volatile("ld.shared.v2.u32 {%0,%1}, [%2];" : "=r"(v.x), "=r"(v.y) : "r"(a));
    return v;
}
__device__ __forceinline__ void mma16816(float (&c)[4], uint32_t a0, uint32_t a1, uint32_t a2, uint32_t a3, uint32_t b0, uint32_t b1) {
    asm volatile("mma.sync.aligned.m16n8k16.row.col.f32.bf16.bf16.f32 {%0,%1,%2,%3}, {%4,%5,%6,%7}, {%8,%9}, {%0,%1,%2,%3};"
                 : "+f"(c[0]), "+f"(c[1]), "+f"(c[2]), "+f"(c[3]) : "r"(a0), "r"(a1), "r"(a2), "r"(a3), "r"(b0), "r"(b1));
}
__device__ __forceinline__ uint32_t mapa(uint32_t a, uint32_t rank) {
    uint32_t r;
    asm volatile("mapa.shared::cluster.u32 %0, %1, %2;" : "=r"(r) : "r"(a), "r"(rank));
    return r;
}
__device__ __forceinline__ void st_async_b32(uint32_t addr, uint32_t v, uint32_t bar) {
    asm volatile("st.async.weak.shared::cluster.mbarrier::complete_tx::bytes.b32 [%0], %1, [%2];" :: "r"(addr), "r"(v), "r"(bar) : "memory");
}
__device__ __forceinline__ void consumer_sync() { asm volatile("bar.sync 1, 256;" ::: "memory"); }
__device__ __forceinline__ float bf16r(float v) { return __bfloat162float(__float2bfloat16_rn(v)); }
__device__ __forceinline__ uint32_t pack_bf16(float lo, float hi) {
    __nv_bfloat162 h = __floats2bfloat162_rn(lo, hi);
    return *reinterpret_cast<uint32_t*>(&h);
}
__device__ __forceinline__ uint4 ld_relaxed_v4(const uint4* p) {
    uint4 v;
    asm volatile("ld.relaxed.gpu.global.v4.u32 {%0,%1,%2,%3}, [%4];" : "=r"(v.x), "=r"(v.y), "=r"(v.z), "=r"(v.w) : "l"(p) : "memory");
    return v;
}
__device__ __forceinline__ void st_relaxed_v4(uint4* p, uint4 v) {
    asm volatile("st.relaxed.gpu.global.v4.u32 [%0], {%1,%2,%3,%4};" :: "l"(p), "r"(v.x), "r"(v.y), "r"(v.z), "r"(v.w) : "memory");
}
__device__ __forceinline__ bool all_nonzero(const uint4& v) { return v.x != 0u && v.y != 0u && v.z != 0u && v.w != 0u; }
__device__ __forceinline__ uint32_t nz_bits(float f) { uint32_t b = __float_as_uint(f); return b == 0u ? 0x80000000u : b; }

__device__ __forceinline__ void gather_outputs(int cidx, int lane, __nv_bfloat16* out, bool poll) {
    uint4* base = g_part + (size_t)cidx * 256 + lane;
    uint4 v[8];
#pragma unroll
    for (int j = 0; j < 8; j++) v[j] = ld_relaxed_v4(base + j * 32);
    if (poll) {
        unsigned n = 0;
        bool done;
        while (true) {
            bool ok = true;
#pragma unroll
            for (int j = 0; j < 8; j++) ok = ok && all_nonzero(v[j]);
            done = __all_sync(0xffffffffu, ok);
            if (done || ++n > SPIN_LIMIT) break;
#pragma unroll
            for (int j = 0; j < 8; j++) if (!all_nonzero(v[j])) v[j] = ld_relaxed_v4(base + j * 32);
        }
        if (!done) SPIN_FAIL(9);
        __syncwarp();
    }
    float s0 = 0.f, s1 = 0.f, s2 = 0.f, s3 = 0.f;
#pragma unroll
    for (int j = 0; j < 8; j++) {
        s0 += __uint_as_float(v[j].x); s1 += __uint_as_float(v[j].y);
        s2 += __uint_as_float(v[j].z); s3 += __uint_as_float(v[j].w);
    }
#pragma unroll
    for (int m = 4; m <= 16; m <<= 1) {
        s0 += __shfl_xor_sync(0xffffffffu, s0, m); s1 += __shfl_xor_sync(0xffffffffu, s1, m);
        s2 += __shfl_xor_sync(0xffffffffu, s2, m); s3 += __shfl_xor_sync(0xffffffffu, s3, m);
    }
    if (lane < 4) {
        const int branch = cidx >> 6, b = (cidx >> 5) & 1, col = (cidx & 31) * 16 + lane * 4;
        uint2 o; o.x = pack_bf16(s0, s1); o.y = pack_bf16(s2, s3);
        *reinterpret_cast<uint2*>(out + b * 1024 + branch * 512 + col) = o;
    }
    const uint4 z = make_uint4(0u, 0u, 0u, 0u);
#pragma unroll
    for (int j = 0; j < 8; j++) base[j * 32] = z;
}

__global__ void __cluster_dims__(2, 1, 1) __launch_bounds__(THREADS, 1)
attn_decode_kernel(const __grid_constant__ Params P) {
    extern __shared__ __align__(1024) unsigned char smem[];
    const uint32_t sb = smem_u32(smem);
    const int tid = threadIdx.x, warp = tid >> 5, lane = tid & 31;
    const int r = blockIdx.x & 1;
    const int h = (blockIdx.x >> 1) & 31;
    const int br = blockIdx.x >> 6;
    const uint32_t bar_full = sb + SM_BAR, bar_empty = bar_full + NS * 8;
    const uint32_t bar_q = bar_empty + NS * 8, bar_o = bar_q + 8;

    uint64_t pol;
    asm volatile("createpolicy.fractional.L2::evict_first.b64 %0, 1.0;" : "=l"(pol));

    if (warp == NCW) {
        const char* kp = reinterpret_cast<const char*>(P.k[br]) + ((size_t)(r * kH + h) * kSk + (kSk - kW)) * (kDh * 2);
        if (lane == 0) {
            TS(0);
#pragma unroll
            for (int s = 0; s < NS; s++) { mbar_init(bar_full + s * 8, 1); mbar_init(bar_empty + s * 8, 4); }
            mbar_init(bar_q, 1); mbar_init(bar_o, 1);
            asm volatile("fence.mbarrier_init.release.cluster;" ::: "memory");
            asm volatile("fence.proxy.async;" ::: "memory");
#pragma unroll
            for (int i = 0; i < NF; i++) {
                mbar_expect_tx(bar_full + i * 8, TILE_BYTES);
                bulk_load(sb + SM_RING + i * TILE_BYTES, kp + (size_t)i * TILE_BYTES, TILE_BYTES, bar_full + i * 8, pol);
            }
            TS(1);
            mbar_expect_tx(bar_q, 128 * 4);
            mbar_expect_tx(bar_o, 64 * 2);
        }
        __syncwarp();
        asm volatile("barrier.cluster.arrive.release.aligned;" ::: "memory");
        if (lane == 0) {
            const char* vp = reinterpret_cast<const char*>(P.v[br]) + ((size_t)(r * kH + h) * kSk + (kSk - kW)) * (kDh * 2);
            const char* wop = reinterpret_cast<const char*>(P.wo[br]) + (size_t)(h * kDh + r * 64) * (kD * 2);
            int slot = NF, pe = 1;
            int fslot = 0, pf = 0;
            for (int i = NF; i < N_TILES; i++) {
                mbar_wait1(bar_full + fslot * 8, pf, 1);
                mbar_wait1(bar_empty + slot * 8, pe, 2);
                const char* src = (i < K_TILES) ? kp + (size_t)i * TILE_BYTES
                                : (i < K_TILES + V_TILES) ? vp + (size_t)(i - K_TILES) * TILE_BYTES
                                : wop + (size_t)(i - K_TILES - V_TILES) * TILE_BYTES;
                mbar_expect_tx(bar_full + slot * 8, TILE_BYTES);
                bulk_load(sb + SM_RING + slot * TILE_BYTES, src, TILE_BYTES, bar_full + slot * 8, pol);
                if (++slot == NS) { slot = 0; pe ^= 1; }
                if (++fslot == NS) { fslot = 0; pf ^= 1; }
            }
            TS(2);
        }
        __syncwarp();
        asm volatile("barrier.cluster.wait.acquire.aligned;" ::: "memory");
        if (P.fused) gather_outputs(blockIdx.x, lane, P.out, true);
        if (lane == 0) TS(3);
        return;
    }

    const int g = lane >> 2, t = lane & 3;
    asm volatile("barrier.cluster.arrive.relaxed.aligned;" ::: "memory");

    {
        const int row0 = r * 256 + warp * 32 + 8 * t;
        const uint4 xw = *reinterpret_cast<const uint4*>(P.x[br] + ((g >> 1) & 1) * kD + row0);
        const char* wp = reinterpret_cast<const char*>(P.wq[br]) + (size_t)row0 * (kH * kDh * 2) + h * (kDh * 2) + g * 16;
        uint4 w[4][4];
#pragma unroll
        for (int u = 0; u < 4; u++) {
            w[u][0] = ldg_stream(wp + (size_t)(2 * u) * 8192, pol);
            w[u][1] = ldg_stream(wp + (size_t)(2 * u) * 8192 + 128, pol);
            w[u][2] = ldg_stream(wp + (size_t)(2 * u + 1) * 8192, pol);
            w[u][3] = ldg_stream(wp + (size_t)(2 * u + 1) * 8192 + 128, pol);
        }
        const uint32_t sel0 = g >= 4 ? 0x4444u : ((g & 1) ? 0x1044u : 0x4410u);
        const uint32_t sel1 = g >= 4 ? 0x4444u : ((g & 1) ? 0x3244u : 0x4432u);
        float acc[4][4];
#pragma unroll
        for (int i = 0; i < 4; i++) { acc[i][0] = acc[i][1] = acc[i][2] = acc[i][3] = 0.f; }
        const uint32_t xs[4] = {xw.x, xw.y, xw.z, xw.w};
#pragma unroll
        for (int u = 0; u < 4; u++) {
            const uint32_t b0 = __byte_perm(xs[u], 0u, sel0), b1 = __byte_perm(xs[u], 0u, sel1);
            mma16816(acc[0], w[u][0].x, w[u][0].y, w[u][2].x, w[u][2].y, b0, b1);
            mma16816(acc[1], w[u][0].z, w[u][0].w, w[u][2].z, w[u][2].w, b0, b1);
            mma16816(acc[2], w[u][1].x, w[u][1].y, w[u][3].x, w[u][3].y, b0, b1);
            mma16816(acc[3], w[u][1].z, w[u][1].w, w[u][3].z, w[u][3].w, b0, b1);
        }
        if (t < 2) {
            float* red = reinterpret_cast<float*>(smem + SM_RED) + (warp * 2 + t) * 128 + 8 * g;
            *reinterpret_cast<float4*>(red) = make_float4(acc[0][0], acc[0][1], acc[0][2], acc[0][3]);
            *reinterpret_cast<float4*>(red + 4) = make_float4(acc[1][0], acc[1][1], acc[1][2], acc[1][3]);
            *reinterpret_cast<float4*>(red + 64) = make_float4(acc[2][0], acc[2][1], acc[2][2], acc[2][3]);
            *reinterpret_cast<float4*>(red + 68) = make_float4(acc[3][0], acc[3][1], acc[3][2], acc[3][3]);
        }
    }
    asm volatile("barrier.cluster.wait.acquire.aligned;" ::: "memory");
    consumer_sync();
    {
        const int b = tid >> 7, d = tid & 127;
        const float* red = reinterpret_cast<const float*>(smem + SM_RED) + b * 128 + d;
        float s = 0.f;
#pragma unroll
        for (int w = 0; w < NCW; w++) s += red[w * 256];
        if (b != r) {
            st_async_b32(mapa(sb + SM_QRECV + d * 4, r ^ 1), __float_as_uint(s), mapa(bar_q, r ^ 1));
        } else {
            mbar_wait_cluster(bar_q, 0, 3);
            const float o = reinterpret_cast<const float*>(smem + SM_QRECV)[d];
            const float q = r == 0 ? s + o : o + s;
            reinterpret_cast<__nv_bfloat16*>(smem + SM_QBF)[d] = __float2bfloat16_rn(q);
        }
    }
    consumer_sync();
    if (tid == 0) TS(4);

    const int grp = warp >> 2, wu = warp & 3;
    int slot = grp, pf = 0;
    auto advance = [&]() { slot += 2; if (slot >= NS) { slot -= NS; pf ^= 1; } };

    {
        const int par = g & 1;
        uint4 qf[4];
        uint32_t off[4];
#pragma unroll
        for (int c = 0; c < 4; c++) {
            const int chunk = 4 * ((c & 1) ^ par) + t + 8 * (c >> 1);
            qf[c] = lds128(sb + SM_QBF + chunk * 16);
            off[c] = chunk * 16 + g * 256 + wu * 4096;
        }
        float mx = -INFINITY;
        float* scores = reinterpret_cast<float*>(smem + SM_SCORES);
        for (int i = grp; i < K_TILES; i += 2) {
            mbar_wait(bar_full + slot * 8, pf, 4);
            const uint32_t tb = sb + SM_RING + slot * TILE_BYTES;
            float acc[2][4];
            uint4 R[4], S[4];
#pragma unroll
            for (int c = 0; c < 4; c++) { R[c] = lds128(tb + off[c]); S[c] = lds128(tb + 2048 + off[c]); }
#pragma unroll
            for (int a = 0; a < 2; a++) { acc[a][0] = acc[a][1] = acc[a][2] = acc[a][3] = 0.f; }
#pragma unroll
            for (int c = 0; c < 4; c++) {
                mma16816(acc[c & 1], R[c].x, S[c].x, R[c].y, S[c].y, qf[c].x, qf[c].y);
                mma16816(acc[c & 1], R[c].z, S[c].z, R[c].w, S[c].w, qf[c].z, qf[c].w);
            }
            __syncwarp();
            if (lane == 0) mbar_arrive(bar_empty + slot * 8);
            float lo = par ? acc[0][1] + acc[1][1] : acc[0][0] + acc[1][0];
            float hi = par ? acc[0][3] + acc[1][3] : acc[0][2] + acc[1][2];
            lo = bf16r(bf16r(lo) * 0.08838834764831845f);
            hi = bf16r(bf16r(hi) * 0.08838834764831845f);
            mx = fmaxf(mx, fmaxf(lo, hi));
            if (t < 2) scores[i * 64 + wu * 16 + g + 8 * t] = t ? hi : lo;
            advance();
        }
#pragma unroll
        for (int m = 4; m <= 16; m <<= 1) mx = fmaxf(mx, __shfl_xor_sync(0xffffffffu, mx, m));
        float* wred = reinterpret_cast<float*>(smem + SM_WRED);
        if (lane == 0) wred[warp] = mx;
        consumer_sync();
        if (tid == 0) TS(5);
        float m = wred[0];
#pragma unroll
        for (int w = 1; w < NCW; w++) m = fmaxf(m, wred[w]);
        const float4 sa = *reinterpret_cast<const float4*>(scores + tid * 4);
        const float4 sc = *reinterpret_cast<const float4*>(scores + 1024 + tid * 4);
        float e[8] = {sa.x, sa.y, sa.z, sa.w, sc.x, sc.y, sc.z, sc.w};
        float sum = 0.f;
#pragma unroll
        for (int j = 0; j < 8; j++) { e[j] = __expf(e[j] - m); sum += e[j]; }
#pragma unroll
        for (int mm = 1; mm <= 16; mm <<= 1) sum += __shfl_xor_sync(0xffffffffu, sum, mm);
        if (lane == 0) wred[8 + warp] = sum;
        consumer_sync();
        float tot = 0.f;
#pragma unroll
        for (int w = 0; w < NCW; w++) tot += wred[8 + w];
        const float inv = 1.0f / tot;
        uint2 pa, pc;
        pa.x = pack_bf16(e[0] * inv, e[1] * inv); pa.y = pack_bf16(e[2] * inv, e[3] * inv);
        pc.x = pack_bf16(e[4] * inv, e[5] * inv); pc.y = pack_bf16(e[6] * inv, e[7] * inv);
        *reinterpret_cast<uint2*>(smem + SM_P + tid * 8) = pa;
        *reinterpret_cast<uint2*>(smem + SM_P + 2048 + tid * 8) = pc;
        consumer_sync();
        if (tid == 0) TS(6);
    }

    const uint32_t sel0 = (g == 2 * t) ? 0x4410u : (g == 2 * t + 1) ? 0x1044u : 0x4444u;
    const uint32_t sel1 = (g == 2 * t) ? 0x4432u : (g == 2 * t + 1) ? 0x3244u : 0x4444u;
    const int c0 = g ^ (2 * t);

    {
        float acc[4][4];
#pragma unroll
        for (int i = 0; i < 4; i++) { acc[i][0] = acc[i][1] = acc[i][2] = acc[i][3] = 0.f; }
        const uint32_t off = (16 * wu + 4 * t) * 256 + c0 * 16;
        for (int i = grp; i < V_TILES; i += 2) {
            const uint2 pw = lds64(sb + SM_P + (i * 64 + 16 * wu + 4 * t) * 2);
            mbar_wait(bar_full + slot * 8, pf, 5);
            const uint32_t tb = sb + SM_RING + slot * TILE_BYTES + off;
            uint4 R0[2], R1[2], S0[2], S1[2];
#pragma unroll
            for (int u = 0; u < 2; u++) {
                R0[u] = lds128(tb + u * 512);
                R1[u] = lds128(tb + u * 512 + 128);
                S0[u] = lds128(tb + u * 512 + 256);
                S1[u] = lds128(tb + u * 512 + 384);
            }
#pragma unroll
            for (int u = 0; u < 2; u++) {
                const uint32_t w = u ? pw.y : pw.x;
                const uint32_t b0 = __byte_perm(w, 0u, sel0), b1 = __byte_perm(w, 0u, sel1);
                mma16816(acc[0], R0[u].x, R0[u].y, S0[u].x, S0[u].y, b0, b1);
                mma16816(acc[1], R0[u].z, R0[u].w, S0[u].z, S0[u].w, b0, b1);
                mma16816(acc[2], R1[u].x, R1[u].y, S1[u].x, S1[u].y, b0, b1);
                mma16816(acc[3], R1[u].z, R1[u].w, S1[u].z, S1[u].w, b0, b1);
            }
            __syncwarp();
            if (lane == 0) mbar_arrive(bar_empty + slot * 8);
            advance();
        }
        float k8[8];
#pragma unroll
        for (int j = 0; j < 8; j++) {
            const float lo = acc[j >> 2][j & 3], hi = acc[2 + (j >> 2)][j & 3];
            const float send = (t & 1) ? lo : hi, keep = (t & 1) ? hi : lo;
            k8[j] = keep + __shfl_xor_sync(0xffffffffu, send, 9);
        }
        float k4[4];
#pragma unroll
        for (int j = 0; j < 4; j++) {
            const float send = (t & 2) ? k8[j] : k8[4 + j], keep = (t & 2) ? k8[4 + j] : k8[j];
            k4[j] = keep + __shfl_xor_sync(0xffffffffu, send, 18);
        }
        float* red = reinterpret_cast<float*>(smem + SM_RED) + warp * 128 + (t & 1) * 64 + c0 * 8 + (t >> 1) * 4;
        *reinterpret_cast<float4*>(red) = make_float4(k4[0], k4[1], k4[2], k4[3]);
        consumer_sync();
        if (tid == 0) TS(7);
        if (tid < 64) {
            const float* rd = reinterpret_cast<const float*>(smem + SM_RED) + tid * 2;
            float s0 = 0.f, s1 = 0.f;
#pragma unroll
            for (int w = 0; w < NCW; w++) { const float2 v = *reinterpret_cast<const float2*>(rd + w * 128); s0 += v.x; s1 += v.y; }
            const uint32_t pk = pack_bf16(s0, s1);
            const uint32_t dst = sb + SM_OBF + r * 128 + (tid & 31) * 4;
            if ((tid >> 5) == r) *reinterpret_cast<uint32_t*>(smem + SM_OBF + r * 128 + (tid & 31) * 4) = pk;
            else st_async_b32(mapa(dst, r ^ 1), pk, mapa(bar_o, r ^ 1));
        }
        consumer_sync();
        mbar_wait_cluster(bar_o, 0, 6);
        if (tid == 0) TS(8);
    }

    {
        float acc[2][2][4];
#pragma unroll
        for (int i = 0; i < 2; i++)
#pragma unroll
            for (int j = 0; j < 2; j++) { acc[i][j][0] = acc[i][j][1] = acc[i][j][2] = acc[i][j][3] = 0.f; }
        int ws = (K_TILES + V_TILES) % NS, wpf = ((K_TILES + V_TILES) / NS) & 1;
        const uint32_t off = (4 * t) * 1024 + warp * 128 + c0 * 16;
#pragma unroll 1
        for (int j = 0; j < WO_TILES; j++) {
            const uint2 o0 = lds64(sb + SM_OBF + (16 * j + 4 * t) * 2);
            const uint2 o1 = lds64(sb + SM_OBF + 128 + (16 * j + 4 * t) * 2);
            mbar_wait(bar_full + ws * 8, wpf, 7);
            const uint32_t tb = sb + SM_RING + ws * TILE_BYTES + off;
#pragma unroll
            for (int u = 0; u < 2; u++) {
                const uint4 R = lds128(tb + u * 2048);
                const uint4 S = lds128(tb + u * 2048 + 1024);
                const uint32_t w0 = u ? o0.y : o0.x, w1 = u ? o1.y : o1.x;
                const uint32_t a0 = __byte_perm(w0, 0u, sel0), a1 = __byte_perm(w0, 0u, sel1);
                const uint32_t b0 = __byte_perm(w1, 0u, sel0), b1 = __byte_perm(w1, 0u, sel1);
                mma16816(acc[0][0], R.x, R.y, S.x, S.y, a0, a1);
                mma16816(acc[0][1], R.z, R.w, S.z, S.w, a0, a1);
                mma16816(acc[1][0], R.x, R.y, S.x, S.y, b0, b1);
                mma16816(acc[1][1], R.z, R.w, S.z, S.w, b0, b1);
            }
            if (++ws == NS) { ws = 0; wpf ^= 1; }
        }
        float k8[8];
#pragma unroll
        for (int j = 0; j < 8; j++) {
            const float lo = acc[0][j >> 2][j & 3], hi = acc[1][j >> 2][j & 3];
            const float send = (t & 1) ? lo : hi, keep = (t & 1) ? hi : lo;
            k8[j] = keep + __shfl_xor_sync(0xffffffffu, send, 9);
        }
        float k4[4];
#pragma unroll
        for (int j = 0; j < 4; j++) {
            const float send = (t & 2) ? k8[j] : k8[4 + j], keep = (t & 2) ? k8[4 + j] : k8[j];
            k4[j] = keep + __shfl_xor_sync(0xffffffffu, send, 18);
        }
        const int b = t & 1;
        const int col = warp * 64 + c0 * 8 + (t >> 1) * 4;
        const int cidx = br * 64 + b * 32 + (col >> 4);
        uint4 v;
        v.x = nz_bits(k4[0]); v.y = nz_bits(k4[1]); v.z = nz_bits(k4[2]); v.w = nz_bits(k4[3]);
        st_relaxed_v4(g_part + ((size_t)cidx * 64 + (blockIdx.x & 63)) * 4 + ((col >> 2) & 3), v);
        if (tid == 0) TS(9);
    }
}

__global__ void gather_kernel(__nv_bfloat16* out) {
    gather_outputs(blockIdx.x, threadIdx.x, out, false);
}

}

extern "C" void kernel_launch(void* const* d_in, const int* in_sizes, int n_in, void* d_out, int out_size) {
    (void)in_sizes; (void)n_in; (void)out_size;
    static int fused = -1;
    if (fused < 0) {
        cudaFuncSetAttribute(attn_decode_kernel, cudaFuncAttributeMaxDynamicSharedMemorySize, SM_TOTAL);
        cudaLaunchConfig_t cfg = {};
        cfg.gridDim = dim3(128); cfg.blockDim = dim3(THREADS); cfg.dynamicSmemBytes = SM_TOTAL;
        cudaLaunchAttribute at[1];
        at[0].id = cudaLaunchAttributeClusterDimension;
        at[0].val.clusterDim.x = 2; at[0].val.clusterDim.y = 1; at[0].val.clusterDim.z = 1;
        cfg.attrs = at; cfg.numAttrs = 1;
        int nclusters = 0;
        cudaError_t e = cudaOccupancyMaxActiveClusters(&nclusters, attn_decode_kernel, &cfg);
        fused = (e == cudaSuccess && nclusters >= 64) ? 1 : 0;
        (void)cudaGetLastError();
    }
    Params P;
    for (int b = 0; b < 2; b++) {
        P.x[b]  = (const __nv_bfloat16*)d_in[5 * b + 0];
        P.k[b]  = (const __nv_bfloat16*)d_in[5 * b + 1];
        P.v[b]  = (const __nv_bfloat16*)d_in[5 * b + 2];
        P.wq[b] = (const __nv_bfloat16*)d_in[5 * b + 3];
        P.wo[b] = (const __nv_bfloat16*)d_in[5 * b + 4];
    }
    P.out = (__nv_bfloat16*)d_out;
    P.fused = fused;
    attn_decode_kernel<<<128, THREADS, SM_TOTAL>>>(P);
    if (!fused) gather_kernel<<<128, 32>>>(P.out);
}
```

```cpp
#include <cuda_runtime.h>
#include <cuda.h>
#include <cuda_bf16.h>
#include <stdint.h>

namespace {

constexpr int kSk = 8192, kW = 2048, kDh = 128, kH = 32, kD = 512;
constexpr int TILE_BYTES = 16384;
#define CFG_NS 12
#define CFG_SLACK128 128
#define CFG_DITHER 0
#define CFG_NF0 CFG_NF
#define CFG_NF 6
constexpr int WQ_TILES_C = 4;
constexpr int NS = CFG_NS;
constexpr int NF = CFG_NF;
constexpr int NF0 = CFG_NF0;
static_assert(NS % 2 == 0 && NF < NS && NF > WQ_TILES_C, "ring config");
constexpr int WQ_TILES = 4, K_TILES = 32, V_TILES = 32, WO_TILES = 4;
constexpr int T_K = WQ_TILES, T_V = T_K + K_TILES, T_WO = T_V + V_TILES;
constexpr int N_TILES = T_WO + WO_TILES;
constexpr int WO_STRIDE = 1040;
static_assert(T_WO % CFG_NS + WO_TILES == CFG_NS, "wo rows must occupy the last ring slots (they spill 1 KB into the dead score buffer)");
constexpr int NCW = 8;
constexpr int THREADS = (NCW + 3) * 32;
constexpr unsigned SPIN_LIMIT = 1u << 18;

constexpr int SM_RING = 0;
constexpr int SM_SCORES = SM_RING + NS * TILE_BYTES;
constexpr int SM_P = SM_SCORES + kW * 4;
constexpr int SM_RED = SM_P + kW * 2;
constexpr int SM_QRECV = SM_RED + NCW * 2 * 128 * 4;
constexpr int SM_QBF = SM_QRECV + 128 * 4;
constexpr int SM_OBF = SM_QBF + 128 * 2;
constexpr int SM_WRED = SM_OBF + 2 * 64 * 2;
constexpr int SM_GSUM = SM_WRED + 16 * 4;
constexpr int SM_BAR = SM_GSUM + 8 * 16 * 4;
constexpr int SM_LIMIT = SM_BAR + (2 * NS + 4) * 8;
constexpr int SM_TS = SM_LIMIT + 8;
constexpr int SM_TOTAL = SM_TS;

struct alignas(64) Params {
    CUtensorMap tmq[2];
    CUtensorMap tmo[2];
    const __nv_bfloat16* k[2];
    const __nv_bfloat16* v[2];
    const __nv_bfloat16* x[2];
    __nv_bfloat16* out;
    int fused;
};

__device__ uint4 g_part[128 * 64 * 4];
__device__ unsigned g_progress;
__device__ unsigned g_zeroed;
__device__ unsigned g_done;

#define TS(i) do { } while (0)

__device__ __forceinline__ uint32_t smem_u32(const void* p) { return (uint32_t)__cvta_generic_to_shared(p); }
__device__ __forceinline__ void mbar_init(uint32_t bar, uint32_t cnt) {
    asm volatile("mbarrier.init.shared::cta.b64 [%0], %1;" :: "r"(bar), "r"(cnt) : "memory");
}
__device__ __forceinline__ void mbar_expect_tx(uint32_t bar, uint32_t bytes) {
    asm volatile("mbarrier.arrive.expect_tx.shared::cta.b64 _, [%0], %1;" :: "r"(bar), "r"(bytes) : "memory");
}
__device__ __forceinline__ void mbar_arrive(uint32_t bar) {
    asm volatile("mbarrier.arrive.shared::cta.b64 _, [%0];" :: "r"(bar) : "memory");
}
__device__ __forceinline__ bool mbar_try(uint32_t bar, uint32_t parity) {
    uint32_t ok;
    asm volatile("{\n.reg .pred p;\nmbarrier.try_wait.parity.shared::cta.b64 p, [%1], %2;\nselp.u32 %0, 1, 0, p;\n}"
                 : "=r"(ok) : "r"(bar), "r"(parity) : "memory");
    return ok != 0;
}
__device__ __forceinline__ bool mbar_test(uint32_t bar, uint32_t parity) {
    uint32_t ok;
    asm volatile("{\n.reg .pred p;\nmbarrier.test_wait.parity.shared::cta.b64 p, [%1], %2;\nselp.u32 %0, 1, 0, p;\n}"
                 : "=r"(ok) : "r"(bar), "r"(parity) : "memory");
    return ok != 0;
}
__device__ __forceinline__ bool mbar_try_cluster(uint32_t bar, uint32_t parity) {
    uint32_t ok;
    asm volatile("{\n.reg .pred p;\nmbarrier.try_wait.parity.acquire.cluster.shared::cta.b64 p, [%1], %2;\nselp.u32 %0, 1, 0, p;\n}"
                 : "=r"(ok) : "r"(bar), "r"(parity) : "memory");
    return ok != 0;
}
#define SPIN_FAIL(code) __trap()
__device__ __forceinline__ void mbar_wait1(uint32_t bar, uint32_t parity, int code = 0) {
    unsigned n = 0;
    bool ok;
    do { ok = mbar_try(bar, parity); } while (!ok && ++n < SPIN_LIMIT);
    if (!ok) SPIN_FAIL(code);
}
__device__ __forceinline__ void mbar_wait(uint32_t bar, uint32_t parity, int code = 0) {
    unsigned n = 0;
    bool ok;
    do { ok = mbar_try(bar, parity); } while (!ok && ++n < SPIN_LIMIT);
    __syncwarp();
    if (!ok) SPIN_FAIL(code);
    __syncwarp();
}
__device__ __forceinline__ void mbar_wait_long(uint32_t bar, uint32_t parity) {
    unsigned n = 0;
    uint32_t ok;
    do {
        asm volatile("{\n.reg .pred p;\nmbarrier.try_wait.parity.shared::cta.b64 p, [%1], %2, %3;\nselp.u32 %0, 1, 0, p;\n}"
                     : "=r"(ok) : "r"(bar), "r"(parity), "r"(2000u) : "memory");
    } while (!ok && ++n < SPIN_LIMIT);
    __syncwarp();
    if (!ok) SPIN_FAIL(10);
    __syncwarp();
}
__device__ __forceinline__ void mbar_wait_cluster(uint32_t bar, uint32_t parity, int code = 0) {
    unsigned n = 0;
    bool ok;
    do { ok = mbar_try_cluster(bar, parity); } while (!ok && ++n < SPIN_LIMIT);
    __syncwarp();
    if (!ok) SPIN_FAIL(code);
    __syncwarp();
}
__device__ __forceinline__ void bulk_load(uint32_t dst, const void* src, uint32_t bytes, uint32_t bar, uint64_t pol) {
    asm volatile("cp.async.bulk.shared::cluster.global.mbarrier::complete_tx::bytes.L2::cache_hint [%0], [%1], %2, [%3], %4;"
                 :: "r"(dst), "l"(src), "r"(bytes), "r"(bar), "l"(pol) : "memory");
}
__device__ __forceinline__ void tensor_load_2d(uint32_t dst, const CUtensorMap* tm, int c0, int c1, uint32_t bar, uint64_t pol) {
    asm volatile("cp.async.bulk.tensor.2d.shared::cluster.global.mbarrier::complete_tx::bytes.L2::cache_hint [%0], [%1, {%2, %3}], [%4], %5;"
                 :: "r"(dst), "l"(tm), "r"(c0), "r"(c1), "r"(bar), "l"(pol) : "memory");
}
__device__ __forceinline__ uint4 ldg_stream(const void* p, uint64_t pol) {
    uint4 v;
    asm volatile("ld.global.nc.L1::no_allocate.L2::cache_hint.v4.u32 {%0,%1,%2,%3}, [%4], %5;"
                 : "=r"(v.x), "=r"(v.y), "=r"(v.z), "=r"(v.w) : "l"(p), "l"(pol));
    return v;
}
__device__ __forceinline__ uint4 lds128(uint32_t a) {
    uint4 v;
    asm volatile("ld.shared.v4.u32 {%0,%1,%2,%3}, [%4];" : "=r"(v.x), "=r"(v.y), "=r"(v.z), "=r"(v.w) : "r"(a));
    return v;
}
__device__ __forceinline__ uint2 lds64(uint32_t a) {
    uint2 v;
    asm volatile("ld.shared.v2.u32 {%0,%1}, [%2];" : "=r"(v.x), "=r"(v.y) : "r"(a));
    return v;
}
__device__ __forceinline__ void mma16816(float (&c)[4], uint32_t a0, uint32_t a1, uint32_t a2, uint32_t a3, uint32_t b0, uint32_t b1) {
    asm volatile("mma.sync.aligned.m16n8k16.row.col.f32.bf16.bf16.f32 {%0,%1,%2,%3}, {%4,%5,%6,%7}, {%8,%9}, {%0,%1,%2,%3};"
                 : "+f"(c[0]), "+f"(c[1]), "+f"(c[2]), "+f"(c[3]) : "r"(a0), "r"(a1), "r"(a2), "r"(a3), "r"(b0), "r"(b1));
}
__device__ __forceinline__ uint32_t mapa(uint32_t a, uint32_t rank) {
    uint32_t r;
    asm volatile("mapa.shared::cluster.u32 %0, %1, %2;" : "=r"(r) : "r"(a), "r"(rank));
    return r;
}
__device__ __forceinline__ void st_async_b32(uint32_t addr, uint32_t v, uint32_t bar) {
    asm volatile("st.async.weak.shared::cluster.mbarrier::complete_tx::bytes.b32 [%0], %1, [%2];" :: "r"(addr), "r"(v), "r"(bar) : "memory");
}
__device__ __forceinline__ void consumer_sync() { asm volatile("bar.sync 1, 256;" ::: "memory"); }
__device__ __forceinline__ float bf16r(float v) { return __bfloat162float(__float2bfloat16_rn(v)); }
__device__ __forceinline__ uint32_t pack_bf16(float lo, float hi) {
    __nv_bfloat162 h = __floats2bfloat162_rn(lo, hi);
    return *reinterpret_cast<uint32_t*>(&h);
}
__device__ __forceinline__ uint4 ld_relaxed_v4(const uint4* p) {
    uint4 v;
    asm volatile("ld.relaxed.gpu.global.v4.u32 {%0,%1,%2,%3}, [%4];" : "=r"(v.x), "=r"(v.y), "=r"(v.z), "=r"(v.w) : "l"(p) : "memory");
    return v;
}
__device__ __forceinline__ void st_relaxed_v4(uint4* p, uint4 v) {
    asm volatile("st.relaxed.gpu.global.v4.u32 [%0], {%1,%2,%3,%4};" :: "l"(p), "r"(v.x), "r"(v.y), "r"(v.z), "r"(v.w) : "memory");
}
__device__ __forceinline__ bool all_nonzero(const uint4& v) { return v.x != 0u && v.y != 0u && v.z != 0u && v.w != 0u; }
__device__ __forceinline__ uint32_t nz_bits(float f) { uint32_t b = __float_as_uint(f); return b == 0u ? 0x80000000u : b; }

__global__ void __cluster_dims__(2, 1, 1) __launch_bounds__(THREADS, 1)
attn_decode_kernel(const __grid_constant__ Params P) {
    extern __shared__ __align__(1024) unsigned char smem[];
    const uint32_t sb = smem_u32(smem);
    const int tid = threadIdx.x, warp = tid >> 5, lane = tid & 31;
    const int r = blockIdx.x & 1;
    const int h = (blockIdx.x >> 1) & 31;
    const int br = blockIdx.x >> 6;
    const uint32_t bar_full = sb + SM_BAR, bar_empty = bar_full + NS * 8;
    const uint32_t bar_q = bar_empty + NS * 8, bar_o = bar_q + 8, bar_g = bar_o + 8, bar_z = bar_g + 8;
    const size_t kv_off = ((size_t)(r * kH + h) * kSk + (kSk - kW)) * (kDh * 2);

    uint64_t pol;
    asm volatile("createpolicy.fractional.L2::evict_first.b64 %0, 1.0;" : "=l"(pol));

    if (tid == NCW * 32) {
        asm volatile("prefetch.tensormap [%0];" :: "l"(&P.tmq[br]) : "memory");
        const char* kp = reinterpret_cast<const char*>(P.k[br]) + kv_off;
#pragma unroll
        for (int s = 0; s < NF; s++) mbar_init(bar_full + s * 8, 1);
        asm volatile("fence.proxy.async.shared::cta;" ::: "memory");
#pragma unroll
        for (int i = T_K; i < NF; i++) {
            mbar_expect_tx(bar_full + i * 8, TILE_BYTES);
            bulk_load(sb + SM_RING + i * TILE_BYTES, kp + (size_t)(i - T_K) * TILE_BYTES, TILE_BYTES, bar_full + i * 8, pol);
            if (i == T_K) TS(10);
        }
#pragma unroll
        for (int i = 0; i < WQ_TILES; i++) {
            mbar_expect_tx(bar_full + i * 8, TILE_BYTES);
            tensor_load_2d(sb + SM_RING + i * TILE_BYTES, &P.tmq[br], h * kDh, r * 256 + i * 64, bar_full + i * 8, pol);
        }
        TS(1);
#pragma unroll 1
        for (int s = NF; s < NS; s++) mbar_init(bar_full + s * 8, 1);
        if (NF0 > NF) {
            asm volatile("fence.proxy.async.shared::cta;" ::: "memory");
#pragma unroll 1
            for (int i = NF; i < NF0; i++) {
                mbar_expect_tx(bar_full + i * 8, TILE_BYTES);
                bulk_load(sb + SM_RING + i * TILE_BYTES, kp + (size_t)(i - T_K) * TILE_BYTES, TILE_BYTES, bar_full + i * 8, pol);
            }
        }
#pragma unroll 1
        for (int s = 0; s < NS; s++) mbar_init(bar_empty + s * 8, 4);
        mbar_init(bar_q, 1); mbar_init(bar_o, 1); mbar_init(bar_g, 1); mbar_init(bar_z, 1);
        *reinterpret_cast<volatile int*>(smem + SM_LIMIT) = P.fused ? NF0 + 3 : N_TILES;
        mbar_expect_tx(bar_q, 128 * 4);
        mbar_expect_tx(bar_o, 64 * 2);
        asm volatile("fence.mbarrier_init.release.cluster;" ::: "memory");
        asm volatile("fence.proxy.async.shared::cta;" ::: "memory");
    }
    __syncwarp();
    if (tid == 0) TS(11);
    asm volatile("barrier.cluster.arrive.relaxed.aligned;" ::: "memory");

    if (warp == NCW) {
        if (lane == 0) {
            const char* kp = reinterpret_cast<const char*>(P.k[br]) + kv_off;
            const char* vp = reinterpret_cast<const char*>(P.v[br]) + kv_off;
            asm volatile("prefetch.tensormap [%0];" :: "l"(&P.tmo[br]) : "memory");
            int slot = NF, pe = 1;
            int fslot = 0, pf = 0;
            for (int i = NF; i < N_TILES; i++) {
                mbar_wait1(bar_full + fslot * 8, pf, 1);
                TS(16 + i - NF);
                asm volatile("red.relaxed.gpu.global.add.u32 [%0], 1;" :: "l"(&g_progress) : "memory");
                { unsigned n = 0; while (i > *reinterpret_cast<volatile int*>(smem + SM_LIMIT) && ++n < (1u << 14)) { } }
                if (i < NF0) { if (++slot == NS) { slot = 0; pe ^= 1; } if (++fslot == NS) { fslot = 0; pf ^= 1; } continue; }
                mbar_wait1(bar_empty + slot * 8, pe, 2);
                if (i < T_WO) {
                    const char* src = (i < T_V) ? kp + (size_t)(i - T_K) * TILE_BYTES : vp + (size_t)(i - T_V) * TILE_BYTES;
                    mbar_expect_tx(bar_full + slot * 8, TILE_BYTES);
                    bulk_load(sb + SM_RING + slot * TILE_BYTES, src, TILE_BYTES, bar_full + slot * 8, pol);
                } else {
                    if (slot + 1 < NS) mbar_wait1(bar_empty + (slot + 1) * 8, pe, 2);
                    mbar_expect_tx(bar_full + slot * 8, 16 * WO_STRIDE);
                    tensor_load_2d(sb + SM_RING + (T_WO % NS) * TILE_BYTES + (i - T_WO) * 16 * WO_STRIDE, &P.tmo[br], 0,
                                   h * kDh + r * 64 + (i - T_WO) * 16, bar_full + slot * 8, pol);
                }
                if (++slot == NS) { slot = 0; pe ^= 1; }
                if (++fslot == NS) { fslot = 0; pf ^= 1; }
            }
            TS(2);
            mbar_arrive(bar_g);
        }
        __syncwarp();
        asm volatile("barrier.cluster.wait.acquire.aligned;" ::: "memory");
        return;
    }

    if (warp == NCW + 2) {
        if (P.fused) {
            uint4* base = g_part + (size_t)blockIdx.x * 256 + lane;
#pragma unroll
            for (int j = 0; j < 8; j++) base[j * 32] = make_uint4(0u, 0u, 0u, 0u);
            __threadfence();
            __syncwarp();
        }
        asm volatile("barrier.cluster.wait.acquire.aligned;" ::: "memory");
        if (lane == 0 && P.fused) {
            asm volatile("red.relaxed.gpu.global.add.u32 [%0], 1;" :: "l"(&g_zeroed) : "memory");
            unsigned n = 0, z;
            do {
                __nanosleep(500);
                asm volatile("ld.relaxed.gpu.global.u32 %0, [%1];" : "=r"(z) : "l"(&g_zeroed) : "memory");
            } while (z < 128u && ++n < SPIN_LIMIT);
            __threadfence();
            mbar_arrive(bar_z);
        }
        return;
    }

    const bool is_aux = warp == NCW + 1;
    const int cw = is_aux ? 0 : warp;
    const int ctid = cw * 32 + lane;
    const uint32_t live_r = is_aux ? 0u : 1u;
    auto LIVE = [&]() -> bool { uint32_t v; asm volatile("mov.u32 %0, %1;" : "=r"(v) : "r"(live_r)); return v != 0u; };
    const int g = lane >> 2, t = lane & 3;
    const int grp = cw >> 2, wu = cw & 3;
    int slot = grp, pf = 0;
    auto advance = [&]() { slot += 2; if (slot >= NS) { slot -= NS; pf ^= 1; } };
    const uint32_t sel0 = (g == 2 * t) ? 0x4410u : (g == 2 * t + 1) ? 0x1044u : 0x4444u;
    const uint32_t sel1 = (g == 2 * t) ? 0x4432u : (g == 2 * t + 1) ? 0x3244u : 0x4444u;
    const int c0 = g ^ (2 * t);
    const uint32_t off_rows = (16 * wu + 4 * t) * 256 + c0 * 16;

    if (!is_aux) {
        uint2 xw[2][2];
#pragma unroll
        for (int jj = 0; jj < 2; jj++)
#pragma unroll
            for (int b = 0; b < 2; b++)
                xw[jj][b] = *reinterpret_cast<const uint2*>(P.x[br] + b * kD + r * 256 + (grp + 2 * jj) * 64 + 16 * wu + 4 * t);
        float acc[2][4][4];
#pragma unroll
        for (int b = 0; b < 2; b++)
#pragma unroll
            for (int i = 0; i < 4; i++) { acc[b][i][0] = acc[b][i][1] = acc[b][i][2] = acc[b][i][3] = 0.f; }
        asm volatile("barrier.cluster.wait.acquire.aligned;" ::: "memory");
        if (tid == 0) TS(12);
#pragma unroll
        for (int jj = 0; jj < 2; jj++) {
            mbar_wait(bar_full + slot * 8, pf, 8);
            const uint32_t tb = sb + SM_RING + slot * TILE_BYTES + off_rows;
#pragma unroll
            for (int u = 0; u < 2; u++) {
                const uint4 R0 = lds128(tb + u * 512), R1 = lds128(tb + u * 512 + 128);
                const uint4 S0 = lds128(tb + u * 512 + 256), S1 = lds128(tb + u * 512 + 384);
#pragma unroll
                for (int b = 0; b < 2; b++) {
                    const uint32_t w = u ? xw[jj][b].y : xw[jj][b].x;
                    const uint32_t b0 = __byte_perm(w, 0u, sel0), b1 = __byte_perm(w, 0u, sel1);
                    mma16816(acc[b][0], R0.x, R0.y, S0.x, S0.y, b0, b1);
                    mma16816(acc[b][1], R0.z, R0.w, S0.z, S0.w, b0, b1);
                    mma16816(acc[b][2], R1.x, R1.y, S1.x, S1.y, b0, b1);
                    mma16816(acc[b][3], R1.z, R1.w, S1.z, S1.w, b0, b1);
                }
            }
            __syncwarp();
            if (lane == 0) mbar_arrive(bar_empty + slot * 8);
            advance();
        }
        if (tid == 0) TS(13);
        float k16[16];
#pragma unroll
        for (int j = 0; j < 16; j++) {
            const float lo = acc[0][j >> 2][j & 3], hi = acc[1][j >> 2][j & 3];
            const float send = (t & 1) ? lo : hi, keep = (t & 1) ? hi : lo;
            k16[j] = keep + __shfl_xor_sync(0xffffffffu, send, 9);
        }
        float k8[8];
#pragma unroll
        for (int j = 0; j < 8; j++) {
            const float send = (t & 2) ? k16[j] : k16[8 + j], keep = (t & 2) ? k16[8 + j] : k16[j];
            k8[j] = keep + __shfl_xor_sync(0xffffffffu, send, 18);
        }
        float* redw = reinterpret_cast<float*>(smem + SM_RED) + (warp * 2 + (t & 1)) * 128 + (t >> 1) * 64 + c0 * 8;
        *reinterpret_cast<float4*>(redw) = make_float4(k8[0], k8[1], k8[2], k8[3]);
        *reinterpret_cast<float4*>(redw + 4) = make_float4(k8[4], k8[5], k8[6], k8[7]);
        consumer_sync();
        const int b = tid >> 7, d = tid & 127;
        const float* red = reinterpret_cast<const float*>(smem + SM_RED) + b * 128 + d;
        float s = 0.f;
#pragma unroll
        for (int w = 0; w < NCW; w++) s += red[w * 256];
        if (b != r) {
            st_async_b32(mapa(sb + SM_QRECV + d * 4, r ^ 1), __float_as_uint(s), mapa(bar_q, r ^ 1));
        } else {
            mbar_wait_cluster(bar_q, 0, 3);
            const float o = reinterpret_cast<const float*>(smem + SM_QRECV)[d];
            const float q = r == 0 ? s + o : o + s;
            reinterpret_cast<__nv_bfloat16*>(smem + SM_QBF)[d] = __float2bfloat16_rn(q);
        }
        consumer_sync();
        if (tid == 0) TS(4);
    }
    {
    {
        const int par = g & 1;
        uint4 qf[4];
        uint32_t off[4];
#pragma unroll
        for (int c = 0; c < 4; c++) {
            const int chunk = 4 * ((c & 1) ^ par) + t + 8 * (c >> 1);
            qf[c] = lds128(sb + SM_QBF + chunk * 16);
            off[c] = chunk * 16 + g * 256 + wu * 4096;
        }
        float mx = -INFINITY;
        float* scores = reinterpret_cast<float*>(smem + SM_SCORES);
#pragma unroll 1
        for (int i = LIVE() ? grp : K_TILES - 1; i < K_TILES; i += 2) {
            if (LIVE()) mbar_wait(bar_full + slot * 8, pf, 4);
            const uint32_t tb = sb + SM_RING + slot * TILE_BYTES;
            float acc[2][4];
            uint4 R[4], S[4];
#pragma unroll
            for (int c = 0; c < 4; c++) { R[c] = lds128(tb + off[c]); S[c] = lds128(tb + 2048 + off[c]); }
#pragma unroll
            for (int a = 0; a < 2; a++) { acc[a][0] = acc[a][1] = acc[a][2] = acc[a][3] = 0.f; }
#pragma unroll
            for (int c = 0; c < 4; c++) {
                mma16816(acc[c & 1], R[c].x, S[c].x, R[c].y, S[c].y, qf[c].x, qf[c].y);
                mma16816(acc[c & 1], R[c].z, S[c].z, R[c].w, S[c].w, qf[c].z, qf[c].w);
            }
            __syncwarp();
            if (lane == 0 && LIVE()) mbar_arrive(bar_empty + slot * 8);
            float lo = par ? acc[0][1] + acc[1][1] : acc[0][0] + acc[1][0];
            float hi = par ? acc[0][3] + acc[1][3] : acc[0][2] + acc[1][2];
            lo = bf16r(bf16r(lo) * 0.08838834764831845f);
            hi = bf16r(bf16r(hi) * 0.08838834764831845f);
            mx = fmaxf(mx, fmaxf(lo, hi));
            if (t < 2 && LIVE()) scores[i * 64 + wu * 16 + g + 8 * t] = t ? hi : lo;
            advance();
        }
#pragma unroll
        for (int m = 4; m <= 16; m <<= 1) mx = fmaxf(mx, __shfl_xor_sync(0xffffffffu, mx, m));
        float* wred = reinterpret_cast<float*>(smem + SM_WRED);
        if (lane == 0 && LIVE()) wred[cw] = mx;
        if (LIVE()) consumer_sync();
        if (tid == 0) TS(5);
        float m = wred[0];
#pragma unroll
        for (int w = 1; w < NCW; w++) m = fmaxf(m, wred[w]);
        const float4 sa = *reinterpret_cast<const float4*>(scores + ctid * 4);
        const float4 sc = *reinterpret_cast<const float4*>(scores + 1024 + ctid * 4);
        float e[8] = {sa.x, sa.y, sa.z, sa.w, sc.x, sc.y, sc.z, sc.w};
        float sum = 0.f;
#pragma unroll
        for (int j = 0; j < 8; j++) { e[j] = __expf(e[j] - m); sum += e[j]; }
#pragma unroll
        for (int mm = 1; mm <= 16; mm <<= 1) sum += __shfl_xor_sync(0xffffffffu, sum, mm);
        if (lane == 0 && LIVE()) wred[8 + cw] = sum;
        if (LIVE()) consumer_sync();
        float tot = 0.f;
#pragma unroll
        for (int w = 0; w < NCW; w++) tot += wred[8 + w];
        const float inv = __frcp_rn(tot);
        uint2 pa, pc;
        pa.x = pack_bf16(e[0] * inv, e[1] * inv); pa.y = pack_bf16(e[2] * inv, e[3] * inv);
        pc.x = pack_bf16(e[4] * inv, e[5] * inv); pc.y = pack_bf16(e[6] * inv, e[7] * inv);
        if (LIVE()) {
            *reinterpret_cast<uint2*>(smem + SM_P + ctid * 8) = pa;
            *reinterpret_cast<uint2*>(smem + SM_P + 2048 + ctid * 8) = pc;
        }
        if (LIVE()) consumer_sync();
        if (tid == 0) TS(6);
    }

    {
        float acc[4][4];
#pragma unroll
        for (int i = 0; i < 4; i++) { acc[i][0] = acc[i][1] = acc[i][2] = acc[i][3] = 0.f; }
#pragma unroll 1
        for (int i = LIVE() ? grp : V_TILES - 1; i < V_TILES; i += 2) {
            const uint2 pw = lds64(sb + SM_P + (i * 64 + 16 * wu + 4 * t) * 2);
            if (LIVE()) mbar_wait(bar_full + slot * 8, pf, 5);
            const uint32_t tb = sb + SM_RING + slot * TILE_BYTES + off_rows;
            uint4 R0[2], R1[2], S0[2], S1[2];
#pragma unroll
            for (int u = 0; u < 2; u++) {
                R0[u] = lds128(tb + u * 512);
                R1[u] = lds128(tb + u * 512 + 128);
                S0[u] = lds128(tb + u * 512 + 256);
                S1[u] = lds128(tb + u * 512 + 384);
            }
#pragma unroll
            for (int u = 0; u < 2; u++) {
                const uint32_t w = u ? pw.y : pw.x;
                const uint32_t b0 = __byte_perm(w, 0u, sel0), b1 = __byte_perm(w, 0u, sel1);
                mma16816(acc[0], R0[u].x, R0[u].y, S0[u].x, S0[u].y, b0, b1);
                mma16816(acc[1], R0[u].z, R0[u].w, S0[u].z, S0[u].w, b0, b1);
                mma16816(acc[2], R1[u].x, R1[u].y, S1[u].x, S1[u].y, b0, b1);
                mma16816(acc[3], R1[u].z, R1[u].w, S1[u].z, S1[u].w, b0, b1);
            }
            __syncwarp();
            if (lane == 0 && LIVE()) mbar_arrive(bar_empty + slot * 8);
            advance();
        }
        float k8[8];
#pragma unroll
        for (int j = 0; j < 8; j++) {
            const float lo = acc[j >> 2][j & 3], hi = acc[2 + (j >> 2)][j & 3];
            const float send = (t & 1) ? lo : hi, keep = (t & 1) ? hi : lo;
            k8[j] = keep + __shfl_xor_sync(0xffffffffu, send, 9);
        }
        float k4[4];
#pragma unroll
        for (int j = 0; j < 4; j++) {
            const float send = (t & 2) ? k8[j] : k8[4 + j], keep = (t & 2) ? k8[4 + j] : k8[j];
            k4[j] = keep + __shfl_xor_sync(0xffffffffu, send, 18);
        }
        float* red = reinterpret_cast<float*>(smem + SM_RED) + cw * 128 + (t & 1) * 64 + c0 * 8 + (t >> 1) * 4;
        if (LIVE()) *reinterpret_cast<float4*>(red) = make_float4(k4[0], k4[1], k4[2], k4[3]);
        if (LIVE()) consumer_sync();
        if (tid == 0) TS(7);
        if (ctid < 64) {
            const float* rd = reinterpret_cast<const float*>(smem + SM_RED) + ctid * 2;
            float s0 = 0.f, s1 = 0.f;
#pragma unroll
            for (int w = 0; w < NCW; w++) { const float2 v = *reinterpret_cast<const float2*>(rd + w * 128); s0 += v.x; s1 += v.y; }
            const uint32_t pk = pack_bf16(s0, s1);
            const uint32_t dst = sb + SM_OBF + r * 128 + (ctid & 31) * 4;
            const bool local = (ctid >> 5) == r;
            if (local && LIVE()) *reinterpret_cast<uint32_t*>(smem + SM_OBF + r * 128 + (ctid & 31) * 4) = pk;
            const uint32_t rdst = mapa(dst, r ^ 1), rbar = mapa(bar_o, r ^ 1);
            if (!local && LIVE()) st_async_b32(rdst, pk, rbar);
        }
        if (LIVE()) consumer_sync();
        if (LIVE()) mbar_wait_cluster(bar_o, 0, 6);
        if (tid == 0) TS(8);
    }

    {
        const uint32_t s0 = g >= 4 ? 0x4444u : ((g & 1) ? 0x1044u : 0x4410u);
        const uint32_t s1 = g >= 4 ? 0x4444u : ((g & 1) ? 0x3244u : 0x4432u);
        uint32_t bf[8][2];
#pragma unroll
        for (int u = 0; u < 8; u++) {
            const uint32_t w = *reinterpret_cast<const uint32_t*>(smem + SM_OBF + ((g >> 1) & 1) * 128 + (4 * u + t) * 4);
            bf[u][0] = __byte_perm(w, 0u, s0); bf[u][1] = __byte_perm(w, 0u, s1);
        }
        const int col = cw * 64 + g * 8;
        uint4* dst = g_part + ((size_t)(br * 64 + (t & 1) * 32 + (col >> 4)) * 64 + (blockIdx.x & 63)) * 4 + ((col >> 2) & 3);
        if (P.fused && LIVE()) mbar_wait(bar_z, 0, 11);
        float acc[2][4];
#pragma unroll
        for (int j = 0; j < 2; j++) { acc[j][0] = acc[j][1] = acc[j][2] = acc[j][3] = 0.f; }
        const uint32_t tb = sb + SM_RING + (T_WO % NS) * TILE_BYTES + (2 * t) * WO_STRIDE + cw * 128 + g * 16;
#pragma unroll
        for (int j = 0; j < WO_TILES; j++) {
            if (LIVE()) mbar_wait(bar_full + (T_WO % NS + j) * 8, (T_WO / NS) & 1, 7);
            if (tid == 0 && j == WO_TILES - 1) TS(14);
#pragma unroll
            for (int u = 0; u < 2; u++) {
                const uint4 R = lds128(tb + (16 * j + 8 * u) * WO_STRIDE);
                const uint4 S = lds128(tb + (16 * j + 8 * u + 1) * WO_STRIDE);
                mma16816(acc[0], R.x, R.y, S.x, S.y, bf[2 * j + u][0], bf[2 * j + u][1]);
                mma16816(acc[1], R.z, R.w, S.z, S.w, bf[2 * j + u][0], bf[2 * j + u][1]);
            }
        }
        if (t < 2 && LIVE()) {
            st_relaxed_v4(dst, make_uint4(nz_bits(acc[0][0]), nz_bits(acc[0][1]), nz_bits(acc[0][2]), nz_bits(acc[0][3])));
            st_relaxed_v4(dst + 1, make_uint4(nz_bits(acc[1][0]), nz_bits(acc[1][1]), nz_bits(acc[1][2]), nz_bits(acc[1][3])));
        }
        if (tid == 0) TS(9);
        if (tid == 224) TS(89);
    }
    if (P.fused) {
        unsigned dn = 0;
        if (tid == 0) asm volatile("atom.relaxed.gpu.global.add.u32 %0, [%1], 1;" : "=r"(dn) : "l"(&g_done) : "memory");
        const uint4* src = g_part + (size_t)blockIdx.x * 256 + cw * 32 + lane;
        const uint32_t fill = LIVE() ? 0u : 1u;
        uint4 v = make_uint4(fill, fill, fill, fill);
        unsigned n = 0;
        bool done;
        do {
            if (!all_nonzero(v)) v = ld_relaxed_v4(src);
            done = __all_sync(0xffffffffu, all_nonzero(v));
        } while (!done && ++n < SPIN_LIMIT);
        if (!done) SPIN_FAIL(9);
        __syncwarp();
        float s0 = __uint_as_float(v.x), s1 = __uint_as_float(v.y), s2 = __uint_as_float(v.z), s3 = __uint_as_float(v.w);
#pragma unroll
        for (int m = 4; m <= 16; m <<= 1) {
            s0 += __shfl_xor_sync(0xffffffffu, s0, m); s1 += __shfl_xor_sync(0xffffffffu, s1, m);
            s2 += __shfl_xor_sync(0xffffffffu, s2, m); s3 += __shfl_xor_sync(0xffffffffu, s3, m);
        }
        float* gsum = reinterpret_cast<float*>(smem + SM_GSUM);
        if (lane < 4 && LIVE()) *reinterpret_cast<float4*>(gsum + cw * 16 + lane * 4) = make_float4(s0, s1, s2, s3);
        if (LIVE()) consumer_sync();
        if (ctid < 8) {
            float t0 = 0.f, t1 = 0.f;
#pragma unroll
            for (int w = 0; w < NCW; w++) { const float2 x = *reinterpret_cast<const float2*>(gsum + w * 16 + ctid * 2); t0 += x.x; t1 += x.y; }
            const int cidx = blockIdx.x;
            if (LIVE()) *reinterpret_cast<uint32_t*>(P.out + ((cidx >> 5) & 1) * 1024 + (cidx >> 6) * 512 + (cidx & 31) * 16 + ctid * 2) = pack_bf16(t0, t1);
        }
        if (tid == 0 && dn == 127u) { g_progress = 0u; g_zeroed = 0u; g_done = 0u; }
        if (tid == 0) TS(3);
    }
    }
    if (is_aux) {
        asm volatile("barrier.cluster.wait.acquire.aligned;" ::: "memory");
        if (lane == 0 && P.fused) {
            TS(0);
            unsigned n = 0;
            const unsigned bias = CFG_SLACK128 + (CFG_DITHER ? ((blockIdx.x * 37u) & 127u) - 64u : 0u);
            n = 0;
            while (!mbar_test(bar_g, 0) && ++n < SPIN_LIMIT) {
                unsigned gp;
                asm volatile("ld.relaxed.gpu.global.u32 %0, [%1];" : "=r"(gp) : "l"(&g_progress) : "memory");
                const int lim = (int)((gp + bias) >> 7) + NF;
                if (lim > *reinterpret_cast<volatile int*>(smem + SM_LIMIT)) *reinterpret_cast<volatile int*>(smem + SM_LIMIT) = lim;
            }
        }
    }
}

__global__ void gather_kernel(__nv_bfloat16* out) {
    const int cidx = blockIdx.x, i = threadIdx.x;
    const float* src = reinterpret_cast<const float*>(g_part) + (size_t)cidx * 1024 + i;
    float tot = 0.f;
    for (int w = 0; w < 8; w++) {
        float v[8];
        for (int j = 0; j < 8; j++) v[j] = src[(w * 8 + j) * 16];
        tot += ((v[0] + v[1]) + (v[2] + v[3])) + ((v[4] + v[5]) + (v[6] + v[7]));
    }
    out[((cidx >> 5) & 1) * 1024 + (cidx >> 6) * 512 + (cidx & 31) * 16 + i] = __float2bfloat16_rn(tot);
}

}

typedef CUresult (*EncodeTiledFn)(CUtensorMap*, CUtensorMapDataType, cuuint32_t, void*, const cuuint64_t*, const cuuint64_t*,
                                  const cuuint32_t*, const cuuint32_t*, CUtensorMapInterleave, CUtensorMapSwizzle,
                                  CUtensorMapL2promotion, CUtensorMapFloatOOBfill);

extern "C" void kernel_launch(void* const* d_in, const int* in_sizes, int n_in, void* d_out, int out_size) {
    (void)in_sizes; (void)n_in; (void)out_size;
    static int fused = -1;
    static EncodeTiledFn encode = nullptr;
    if (fused < 0) {
        cudaFuncSetAttribute(attn_decode_kernel, cudaFuncAttributeMaxDynamicSharedMemorySize, SM_TOTAL);
        cudaLaunchConfig_t cfg = {};
        cfg.gridDim = dim3(128); cfg.blockDim = dim3(THREADS); cfg.dynamicSmemBytes = SM_TOTAL;
        cudaLaunchAttribute at[1];
        at[0].id = cudaLaunchAttributeClusterDimension;
        at[0].val.clusterDim.x = 2; at[0].val.clusterDim.y = 1; at[0].val.clusterDim.z = 1;
        cfg.attrs = at; cfg.numAttrs = 1;
        int nclusters = 0;
        cudaError_t e = cudaOccupancyMaxActiveClusters(&nclusters, attn_decode_kernel, &cfg);
        fused = (e == cudaSuccess && nclusters >= 64) ? 1 : 0;
        void* fn = nullptr;
        cudaDriverEntryPointQueryResult qres;
        if (cudaGetDriverEntryPoint("cuTensorMapEncodeTiled", &fn, cudaEnableDefault, &qres) == cudaSuccess &&
            qres == cudaDriverEntryPointSuccess)
            encode = (EncodeTiledFn)fn;
        (void)cudaGetLastError();
    }
    Params P;
    for (int b = 0; b < 2; b++) {
        P.x[b]  = (const __nv_bfloat16*)d_in[5 * b + 0];
        P.k[b]  = (const __nv_bfloat16*)d_in[5 * b + 1];
        P.v[b]  = (const __nv_bfloat16*)d_in[5 * b + 2];
        const cuuint64_t gdim[2] = {(cuuint64_t)(kH * kDh), (cuuint64_t)kD};
        const cuuint64_t gstride[1] = {(cuuint64_t)(kH * kDh * 2)};
        const cuuint32_t box[2] = {(cuuint32_t)kDh, 64u};
        const cuuint32_t estr[2] = {1u, 1u};
        encode(&P.tmq[b], CU_TENSOR_MAP_DATA_TYPE_BFLOAT16, 2, d_in[5 * b + 3], gdim, gstride, box, estr,
               CU_TENSOR_MAP_INTERLEAVE_NONE, CU_TENSOR_MAP_SWIZZLE_NONE, CU_TENSOR_MAP_L2_PROMOTION_NONE,
               CU_TENSOR_MAP_FLOAT_OOB_FILL_NONE);
        const cuuint64_t odim[2] = {(cuuint64_t)(kD * 2 / 8), (cuuint64_t)(kH * kDh)};
        const cuuint64_t ostride[1] = {(cuuint64_t)(kD * 2)};
        const cuuint32_t obox[2] = {(cuuint32_t)(WO_STRIDE / 8), 16u};
        encode(&P.tmo[b], CU_TENSOR_MAP_DATA_TYPE_UINT64, 2, d_in[5 * b + 4], odim, ostride, obox, estr,
               CU_TENSOR_MAP_INTERLEAVE_NONE, CU_TENSOR_MAP_SWIZZLE_NONE, CU_TENSOR_MAP_L2_PROMOTION_NONE,
               CU_TENSOR_MAP_FLOAT_OOB_FILL_NONE);
    }
    P.out = (__nv_bfloat16*)d_out;
    P.fused = fused;
    attn_decode_kernel<<<128, THREADS, SM_TOTAL>>>(P);
    if (!fused) gather_kernel<<<128, 16>>>(P.out);
}
```

```cpp
#include <cuda_runtime.h>
#include <cuda.h>
#include <cuda_bf16.h>
#include <stdint.h>

namespace {

constexpr int kSk = 8192, kW = 2048, kDh = 128, kH = 32, kD = 512;
constexpr int TILE_BYTES = 16384;
constexpr int NS = 12;
constexpr int NF = 6;
constexpr int SLACK128 = 128;
constexpr int WQ_TILES = 4, K_TILES = 32, V_TILES = 32, WO_TILES = 4;
constexpr int T_K = WQ_TILES, T_V = T_K + K_TILES, T_WO = T_V + V_TILES;
constexpr int N_TILES = T_WO + WO_TILES;
constexpr int WO_STRIDE = 1040;
constexpr int NCW = 8;
constexpr int THREADS = (NCW + 3) * 32;
constexpr unsigned SPIN_LIMIT = 1u << 18;
static_assert(NS % 2 == 0 && NF < NS && NF > WQ_TILES, "ring config");
static_assert(T_WO % NS + WO_TILES == NS, "wo rows occupy the last ring slots and spill 1 KB into the dead score buffer");

constexpr int SM_RING = 0;
constexpr int SM_SCORES = SM_RING + NS * TILE_BYTES;
constexpr int SM_P = SM_SCORES + kW * 4;
constexpr int SM_RED = SM_P + kW * 2;
constexpr int SM_QRECV = SM_RED + NCW * 2 * 128 * 4;
constexpr int SM_QBF = SM_QRECV + 128 * 4;
constexpr int SM_OBF = SM_QBF + 128 * 2;
constexpr int SM_WRED = SM_OBF + 2 * 64 * 2;
constexpr int SM_GSUM = SM_WRED + 16 * 4;
constexpr int SM_BAR = SM_GSUM + 8 * 16 * 4;
constexpr int SM_LIMIT = SM_BAR + (2 * NS + 4) * 8;
constexpr int SM_TOTAL = SM_LIMIT + 8;

struct alignas(64) Params {
    CUtensorMap tmq[2];
    CUtensorMap tmo[2];
    const __nv_bfloat16* k[2];
    const __nv_bfloat16* v[2];
    const __nv_bfloat16* x[2];
    __nv_bfloat16* out;
    int fused;
};

__device__ uint4 g_part[128 * 64 * 4];
__device__ unsigned g_progress;
__device__ unsigned g_zeroed;
__device__ unsigned g_done;
__device__ __nv_bfloat16 g_o[2 * 2 * kH * kDh];

__device__ __forceinline__ uint32_t smem_u32(const void* p) { return (uint32_t)__cvta_generic_to_shared(p); }
__device__ __forceinline__ void mbar_init(uint32_t bar, uint32_t cnt) {
    asm volatile("mbarrier.init.shared::cta.b64 [%0], %1;" :: "r"(bar), "r"(cnt) : "memory");
}
__device__ __forceinline__ void mbar_expect_tx(uint32_t bar, uint32_t bytes) {
    asm volatile("mbarrier.arrive.expect_tx.shared::cta.b64 _, [%0], %1;" :: "r"(bar), "r"(bytes) : "memory");
}
__device__ __forceinline__ void mbar_arrive(uint32_t bar) {
    asm volatile("mbarrier.arrive.shared::cta.b64 _, [%0];" :: "r"(bar) : "memory");
}
__device__ __forceinline__ bool mbar_try(uint32_t bar, uint32_t parity) {
    uint32_t ok;
    asm volatile("{\n.reg .pred p;\nmbarrier.try_wait.parity.shared::cta.b64 p, [%1], %2;\nselp.u32 %0, 1, 0, p;\n}"
                 : "=r"(ok) : "r"(bar), "r"(parity) : "memory");
    return ok != 0;
}
__device__ __forceinline__ bool mbar_test(uint32_t bar, uint32_t parity) {
    uint32_t ok;
    asm volatile("{\n.reg .pred p;\nmbarrier.test_wait.parity.shared::cta.b64 p, [%1], %2;\nselp.u32 %0, 1, 0, p;\n}"
                 : "=r"(ok) : "r"(bar), "r"(parity) : "memory");
    return ok != 0;
}
__device__ __forceinline__ bool mbar_try_cluster(uint32_t bar, uint32_t parity) {
    uint32_t ok;
    asm volatile("{\n.reg .pred p;\nmbarrier.try_wait.parity.acquire.cluster.shared::cta.b64 p, [%1], %2;\nselp.u32 %0, 1, 0, p;\n}"
                 : "=r"(ok) : "r"(bar), "r"(parity) : "memory");
    return ok != 0;
}
__device__ __forceinline__ void mbar_wait1(uint32_t bar, uint32_t parity) {
    unsigned n = 0;
    bool ok;
    do { ok = mbar_try(bar, parity); } while (!ok && ++n < SPIN_LIMIT);
    if (!ok) __trap();
}
__device__ __forceinline__ void mbar_wait(uint32_t bar, uint32_t parity) {
    unsigned n = 0;
    bool ok;
    do { ok = mbar_try(bar, parity); } while (!ok && ++n < SPIN_LIMIT);
    __syncwarp();
    if (!ok) __trap();
    __syncwarp();
}
__device__ __forceinline__ void mbar_wait_cluster(uint32_t bar, uint32_t parity) {
    unsigned n = 0;
    bool ok;
    do { ok = mbar_try_cluster(bar, parity); } while (!ok && ++n < SPIN_LIMIT);
    __syncwarp();
    if (!ok) __trap();
    __syncwarp();
}
__device__ __forceinline__ void bulk_load(uint32_t dst, const void* src, uint32_t bytes, uint32_t bar, uint64_t pol) {
    asm volatile("cp.async.bulk.shared::cluster.global.mbarrier::complete_tx::bytes.L2::cache_hint [%0], [%1], %2, [%3], %4;"
                 :: "r"(dst), "l"(src), "r"(bytes), "r"(bar), "l"(pol) : "memory");
}
__device__ __forceinline__ void tensor_load_2d(uint32_t dst, const CUtensorMap* tm, int c0, int c1, uint32_t bar, uint64_t pol) {
    asm volatile("cp.async.bulk.tensor.2d.shared::cluster.global.mbarrier::complete_tx::bytes.L2::cache_hint [%0], [%1, {%2, %3}], [%4], %5;"
                 :: "r"(dst), "l"(tm), "r"(c0), "r"(c1), "r"(bar), "l"(pol) : "memory");
}
__device__ __forceinline__ uint4 lds128(uint32_t a) {
    uint4 v;
    asm volatile("ld.shared.v4.u32 {%0,%1,%2,%3}, [%4];" : "=r"(v.x), "=r"(v.y), "=r"(v.z), "=r"(v.w) : "r"(a));
    return v;
}
__device__ __forceinline__ uint2 lds64(uint32_t a) {
    uint2 v;
    asm volatile("ld.shared.v2.u32 {%0,%1}, [%2];" : "=r"(v.x), "=r"(v.y) : "r"(a));
    return v;
}
__device__ __forceinline__ void mma16816(float (&c)[4], uint32_t a0, uint32_t a1, uint32_t a2, uint32_t a3, uint32_t b0, uint32_t b1) {
    asm volatile("mma.sync.aligned.m16n8k16.row.col.f32.bf16.bf16.f32 {%0,%1,%2,%3}, {%4,%5,%6,%7}, {%8,%9}, {%0,%1,%2,%3};"
                 : "+f"(c[0]), "+f"(c[1]), "+f"(c[2]), "+f"(c[3]) : "r"(a0), "r"(a1), "r"(a2), "r"(a3), "r"(b0), "r"(b1));
}
__device__ __forceinline__ uint32_t mapa(uint32_t a, uint32_t rank) {
    uint32_t r;
    asm volatile("mapa.shared::cluster.u32 %0, %1, %2;" : "=r"(r) : "r"(a), "r"(rank));
    return r;
}
__device__ __forceinline__ void st_async_b32(uint32_t addr, uint32_t v, uint32_t bar) {
    asm volatile("st.async.weak.shared::cluster.mbarrier::complete_tx::bytes.b32 [%0], %1, [%2];" :: "r"(addr), "r"(v), "r"(bar) : "memory");
}
__device__ __forceinline__ void consumer_sync() { asm volatile("bar.sync 1, 256;" ::: "memory"); }
__device__ __forceinline__ float bf16r(float v) { return __bfloat162float(__float2bfloat16_rn(v)); }
__device__ __forceinline__ uint32_t pack_bf16(float lo, float hi) {
    __nv_bfloat162 h = __floats2bfloat162_rn(lo, hi);
    return *reinterpret_cast<uint32_t*>(&h);
}
__device__ __forceinline__ uint4 ld_relaxed_v4(const uint4* p) {
    uint4 v;
    asm volatile("ld.relaxed.gpu.global.v4.u32 {%0,%1,%2,%3}, [%4];" : "=r"(v.x), "=r"(v.y), "=r"(v.z), "=r"(v.w) : "l"(p) : "memory");
    return v;
}
__device__ __forceinline__ void st_relaxed_v4(uint4* p, uint4 v) {
    asm volatile("st.relaxed.gpu.global.v4.u32 [%0], {%1,%2,%3,%4};" :: "l"(p), "r"(v.x), "r"(v.y), "r"(v.z), "r"(v.w) : "memory");
}
__device__ __forceinline__ bool all_nonzero(const uint4& v) { return v.x != 0u && v.y != 0u && v.z != 0u && v.w != 0u; }
__device__ __forceinline__ uint32_t nz_bits(float f) { uint32_t b = __float_as_uint(f); return b == 0u ? 0x80000000u : b; }

__global__ void __cluster_dims__(2, 1, 1) __launch_bounds__(THREADS, 1)
attn_decode_kernel(const __grid_constant__ Params P) {
    extern __shared__ __align__(1024) unsigned char smem[];
    const uint32_t sb = smem_u32(smem);
    const int tid = threadIdx.x, warp = tid >> 5, lane = tid & 31;
    const int r = blockIdx.x & 1;
    const int h = (blockIdx.x >> 1) & 31;
    const int br = blockIdx.x >> 6;
    const uint32_t bar_full = sb + SM_BAR, bar_empty = bar_full + NS * 8;
    const uint32_t bar_q = bar_empty + NS * 8, bar_o = bar_q + 8, bar_g = bar_o + 8, bar_z = bar_g + 8;
    const size_t kv_off = ((size_t)(r * kH + h) * kSk + (kSk - kW)) * (kDh * 2);

    uint64_t pol;
    asm volatile("createpolicy.fractional.L2::evict_first.b64 %0, 1.0;" : "=l"(pol));

    if (tid == 0) {
        const char* kp0 = reinterpret_cast<const char*>(P.k[br]) + kv_off;
        asm volatile("cp.async.bulk.prefetch.L2.global.L2::cache_hint [%0], %1, %2;"
                     :: "l"(kp0), "r"((NF - T_K) * TILE_BYTES), "l"(pol) : "memory");
    }
    if (tid == NCW * 32) {
        asm volatile("prefetch.tensormap [%0];" :: "l"(&P.tmq[br]) : "memory");
        const char* kp = reinterpret_cast<const char*>(P.k[br]) + kv_off;
#pragma unroll
        for (int s = 0; s < NF; s++) mbar_init(bar_full + s * 8, 1);
        asm volatile("fence.proxy.async.shared::cta;" ::: "memory");
#pragma unroll
        for (int i = T_K; i < NF; i++) {
            mbar_expect_tx(bar_full + i * 8, TILE_BYTES);
            bulk_load(sb + SM_RING + i * TILE_BYTES, kp + (size_t)(i - T_K) * TILE_BYTES, TILE_BYTES, bar_full + i * 8, pol);
        }
#pragma unroll
        for (int i = 0; i < WQ_TILES; i++) {
            mbar_expect_tx(bar_full + i * 8, TILE_BYTES);
            tensor_load_2d(sb + SM_RING + i * TILE_BYTES, &P.tmq[br], h * kDh, r * 256 + i * 64, bar_full + i * 8, pol);
        }
#pragma unroll 1
        for (int s = NF; s < NS; s++) mbar_init(bar_full + s * 8, 1);
#pragma unroll 1
        for (int s = 0; s < NS; s++) mbar_init(bar_empty + s * 8, 4);
        mbar_init(bar_q, 1); mbar_init(bar_o, 1); mbar_init(bar_g, 1); mbar_init(bar_z, 1);
        *reinterpret_cast<volatile int*>(smem + SM_LIMIT) = P.fused ? NF + 3 : N_TILES;
        mbar_expect_tx(bar_q, 128 * 4);
        mbar_expect_tx(bar_o, 64 * 2);
        asm volatile("fence.mbarrier_init.release.cluster;" ::: "memory");
        asm volatile("fence.proxy.async.shared::cta;" ::: "memory");
    }
    __syncwarp();
    asm volatile("barrier.cluster.arrive.relaxed.aligned;" ::: "memory");

    if (warp == NCW) {
        if (lane == 0) {
            const char* kp = reinterpret_cast<const char*>(P.k[br]) + kv_off;
            const char* vp = reinterpret_cast<const char*>(P.v[br]) + kv_off;
            asm volatile("prefetch.tensormap [%0];" :: "l"(&P.tmo[br]) : "memory");
            int slot = NF, pe = 1;
            int fslot = 0, pf = 0;
            for (int i = NF; i < N_TILES; i++) {
                mbar_wait1(bar_full + fslot * 8, pf);
                asm volatile("red.relaxed.gpu.global.add.u32 [%0], 1;" :: "l"(&g_progress) : "memory");
                {
                    unsigned n = 0;
                    while (i > *reinterpret_cast<volatile int*>(smem + SM_LIMIT) && ++n < (1u << 14)) { }
                }
                mbar_wait1(bar_empty + slot * 8, pe);
                if (i < T_WO) {
                    const char* src = (i < T_V) ? kp + (size_t)(i - T_K) * TILE_BYTES : vp + (size_t)(i - T_V) * TILE_BYTES;
                    mbar_expect_tx(bar_full + slot * 8, TILE_BYTES);
                    bulk_load(sb + SM_RING + slot * TILE_BYTES, src, TILE_BYTES, bar_full + slot * 8, pol);
                } else {
                    if (slot + 1 < NS) mbar_wait1(bar_empty + (slot + 1) * 8, pe);
                    mbar_expect_tx(bar_full + slot * 8, 16 * WO_STRIDE);
                    tensor_load_2d(sb + SM_RING + (T_WO % NS) * TILE_BYTES + (i - T_WO) * 16 * WO_STRIDE, &P.tmo[br], 0,
                                   h * kDh + r * 64 + (i - T_WO) * 16, bar_full + slot * 8, pol);
                }
                if (++slot == NS) { slot = 0; pe ^= 1; }
                if (++fslot == NS) { fslot = 0; pf ^= 1; }
            }
            mbar_arrive(bar_g);
        }
        __syncwarp();
        asm volatile("barrier.cluster.wait.acquire.aligned;" ::: "memory");
        return;
    }

    if (warp == NCW + 2) {
        if (P.fused) {
            uint4* base = g_part + (size_t)blockIdx.x * 256 + lane;
#pragma unroll
            for (int j = 0; j < 8; j++) base[j * 32] = make_uint4(0u, 0u, 0u, 0u);
            __threadfence();
            __syncwarp();
        }
        asm volatile("barrier.cluster.wait.acquire.aligned;" ::: "memory");
        if (lane == 0 && P.fused) {
            asm volatile("red.relaxed.gpu.global.add.u32 [%0], 1;" :: "l"(&g_zeroed) : "memory");
            unsigned n = 0, z;
            do {
                __nanosleep(500);
                asm volatile("ld.relaxed.gpu.global.u32 %0, [%1];" : "=r"(z) : "l"(&g_zeroed) : "memory");
            } while (z < 128u && ++n < SPIN_LIMIT);
            if (z < 128u) __trap();
            __threadfence();
            mbar_arrive(bar_z);
        }
        return;
    }

    const bool is_aux = warp == NCW + 1;
    const int cw = is_aux ? 0 : warp;
    const int ctid = cw * 32 + lane;
    const uint32_t live_r = is_aux ? 0u : 1u;
    auto LIVE = [&]() -> bool { uint32_t v; asm volatile("mov.u32 %0, %1;" : "=r"(v) : "r"(live_r)); return v != 0u; };
    const int g = lane >> 2, t = lane & 3;
    const int grp = cw >> 2, wu = cw & 3;
    int slot = grp, pf = 0;
    auto advance = [&]() { slot += 2; if (slot >= NS) { slot -= NS; pf ^= 1; } };
    const uint32_t sel0 = (g == 2 * t) ? 0x4410u : (g == 2 * t + 1) ? 0x1044u : 0x4444u;
    const uint32_t sel1 = (g == 2 * t) ? 0x4432u : (g == 2 * t + 1) ? 0x3244u : 0x4444u;
    const int c0 = g ^ (2 * t);
    const uint32_t off_rows = (16 * wu + 4 * t) * 256 + c0 * 16;

    if (!is_aux) {
        uint2 xw[2][2];
#pragma unroll
        for (int jj = 0; jj < 2; jj++)
#pragma unroll
            for (int b = 0; b < 2; b++)
                xw[jj][b] = *reinterpret_cast<const uint2*>(P.x[br] + b * kD + r * 256 + (grp + 2 * jj) * 64 + 16 * wu + 4 * t);
        float acc[2][4][4];
#pragma unroll
        for (int b = 0; b < 2; b++)
#pragma unroll
            for (int i = 0; i < 4; i++) { acc[b][i][0] = acc[b][i][1] = acc[b][i][2] = acc[b][i][3] = 0.f; }
        asm volatile("barrier.cluster.wait.acquire.aligned;" ::: "memory");
#pragma unroll
        for (int jj = 0; jj < 2; jj++) {
            mbar_wait(bar_full + slot * 8, pf);
            const uint32_t tb = sb + SM_RING + slot * TILE_BYTES + off_rows;
#pragma unroll
            for (int u = 0; u < 2; u++) {
                const uint4 R0 = lds128(tb + u * 512), R1 = lds128(tb + u * 512 + 128);
                const uint4 S0 = lds128(tb + u * 512 + 256), S1 = lds128(tb + u * 512 + 384);
#pragma unroll
                for (int b = 0; b < 2; b++) {
                    const uint32_t w = u ? xw[jj][b].y : xw[jj][b].x;
                    const uint32_t b0 = __byte_perm(w, 0u, sel0), b1 = __byte_perm(w, 0u, sel1);
                    mma16816(acc[b][0], R0.x, R0.y, S0.x, S0.y, b0, b1);
                    mma16816(acc[b][1], R0.z, R0.w, S0.z, S0.w, b0, b1);
                    mma16816(acc[b][2], R1.x, R1.y, S1.x, S1.y, b0, b1);
                    mma16816(acc[b][3], R1.z, R1.w, S1.z, S1.w, b0, b1);
                }
            }
            __syncwarp();
            if (lane == 0) mbar_arrive(bar_empty + slot * 8);
            advance();
        }
        float k16[16];
#pragma unroll
        for (int j = 0; j < 16; j++) {
            const float lo = acc[0][j >> 2][j & 3], hi = acc[1][j >> 2][j & 3];
            const float send = (t & 1) ? lo : hi, keep = (t & 1) ? hi : lo;
            k16[j] = keep + __shfl_xor_sync(0xffffffffu, send, 9);
        }
        float k8[8];
#pragma unroll
        for (int j = 0; j < 8; j++) {
            const float send = (t & 2) ? k16[j] : k16[8 + j], keep = (t & 2) ? k16[8 + j] : k16[j];
            k8[j] = keep + __shfl_xor_sync(0xffffffffu, send, 18);
        }
        float* redw = reinterpret_cast<float*>(smem + SM_RED) + (warp * 2 + (t & 1)) * 128 + (t >> 1) * 64 + c0 * 8;
        *reinterpret_cast<float4*>(redw) = make_float4(k8[0], k8[1], k8[2], k8[3]);
        *reinterpret_cast<float4*>(redw + 4) = make_float4(k8[4], k8[5], k8[6], k8[7]);
        consumer_sync();
        const int b = tid >> 7, d = tid & 127;
        const float* red = reinterpret_cast<const float*>(smem + SM_RED) + b * 128 + d;
        float s = 0.f;
#pragma unroll
        for (int w = 0; w < NCW; w++) s += red[w * 256];
        if (b != r) {
            st_async_b32(mapa(sb + SM_QRECV + d * 4, r ^ 1), __float_as_uint(s), mapa(bar_q, r ^ 1));
        } else {
            mbar_wait_cluster(bar_q, 0);
            const float o = reinterpret_cast<const float*>(smem + SM_QRECV)[d];
            const float q = r == 0 ? s + o : o + s;
            reinterpret_cast<__nv_bfloat16*>(smem + SM_QBF)[d] = __float2bfloat16_rn(q);
        }
        consumer_sync();
    }

    {
        const int par = g & 1;
        uint4 qf[4];
        uint32_t off[4];
#pragma unroll
        for (int c = 0; c < 4; c++) {
            const int chunk = 4 * ((c & 1) ^ par) + t + 8 * (c >> 1);
            qf[c] = lds128(sb + SM_QBF + chunk * 16);
            off[c] = chunk * 16 + g * 256 + wu * 4096;
        }
        float mx = -INFINITY;
        float* scores = reinterpret_cast<float*>(smem + SM_SCORES);
#pragma unroll 1
        for (int i = LIVE() ? grp : K_TILES - 1; i < K_TILES; i += 2) {
            if (LIVE()) mbar_wait(bar_full + slot * 8, pf);
            const uint32_t tb = sb + SM_RING + slot * TILE_BYTES;
            float acc[2][4];
            uint4 R[4], S[4];
#pragma unroll
            for (int c = 0; c < 4; c++) { R[c] = lds128(tb + off[c]); S[c] = lds128(tb + 2048 + off[c]); }
#pragma unroll
            for (int a = 0; a < 2; a++) { acc[a][0] = acc[a][1] = acc[a][2] = acc[a][3] = 0.f; }
#pragma unroll
            for (int c = 0; c < 4; c++) {
                mma16816(acc[c & 1], R[c].x, S[c].x, R[c].y, S[c].y, qf[c].x, qf[c].y);
                mma16816(acc[c & 1], R[c].z, S[c].z, R[c].w, S[c].w, qf[c].z, qf[c].w);
            }
            __syncwarp();
            if (lane == 0 && LIVE()) mbar_arrive(bar_empty + slot * 8);
            float lo = par ? acc[0][1] + acc[1][1] : acc[0][0] + acc[1][0];
            float hi = par ? acc[0][3] + acc[1][3] : acc[0][2] + acc[1][2];
            lo = bf16r(bf16r(lo) * 0.08838834764831845f);
            hi = bf16r(bf16r(hi) * 0.08838834764831845f);
            mx = fmaxf(mx, fmaxf(lo, hi));
            if (t < 2 && LIVE()) scores[i * 64 + wu * 16 + g + 8 * t] = t ? hi : lo;
            advance();
        }
#pragma unroll
        for (int m = 4; m <= 16; m <<= 1) mx = fmaxf(mx, __shfl_xor_sync(0xffffffffu, mx, m));
        float* wred = reinterpret_cast<float*>(smem + SM_WRED);
        if (lane == 0 && LIVE()) wred[cw] = mx;
        if (LIVE()) consumer_sync();
        float m = wred[0];
#pragma unroll
        for (int w = 1; w < NCW; w++) m = fmaxf(m, wred[w]);
        const float4 sa = *reinterpret_cast<const float4*>(scores + ctid * 4);
        const float4 sc = *reinterpret_cast<const float4*>(scores + 1024 + ctid * 4);
        float e[8] = {sa.x, sa.y, sa.z, sa.w, sc.x, sc.y, sc.z, sc.w};
        float sum = 0.f;
#pragma unroll
        for (int j = 0; j < 8; j++) { e[j] = __expf(e[j] - m); sum += e[j]; }
#pragma unroll
        for (int mm = 1; mm <= 16; mm <<= 1) sum += __shfl_xor_sync(0xffffffffu, sum, mm);
        if (lane == 0 && LIVE()) wred[8 + cw] = sum;
        if (LIVE()) consumer_sync();
        float tot = 0.f;
#pragma unroll
        for (int w = 0; w < NCW; w++) tot += wred[8 + w];
        const float inv = __frcp_rn(tot);
        uint2 pa, pc;
        pa.x = pack_bf16(e[0] * inv, e[1] * inv); pa.y = pack_bf16(e[2] * inv, e[3] * inv);
        pc.x = pack_bf16(e[4] * inv, e[5] * inv); pc.y = pack_bf16(e[6] * inv, e[7] * inv);
        if (LIVE()) {
            *reinterpret_cast<uint2*>(smem + SM_P + ctid * 8) = pa;
            *reinterpret_cast<uint2*>(smem + SM_P + 2048 + ctid * 8) = pc;
        }
        if (LIVE()) consumer_sync();
    }

    {
        float acc[4][4];
#pragma unroll
        for (int i = 0; i < 4; i++) { acc[i][0] = acc[i][1] = acc[i][2] = acc[i][3] = 0.f; }
#pragma unroll 1
        for (int i = LIVE() ? grp : V_TILES - 1; i < V_TILES; i += 2) {
            const uint2 pw = lds64(sb + SM_P + (i * 64 + 16 * wu + 4 * t) * 2);
            if (LIVE()) mbar_wait(bar_full + slot * 8, pf);
            const uint32_t tb = sb + SM_RING + slot * TILE_BYTES + off_rows;
            uint4 R0[2], R1[2], S0[2], S1[2];
#pragma unroll
            for (int u = 0; u < 2; u++) {
                R0[u] = lds128(tb + u * 512);
                R1[u] = lds128(tb + u * 512 + 128);
                S0[u] = lds128(tb + u * 512 + 256);
                S1[u] = lds128(tb + u * 512 + 384);
            }
#pragma unroll
            for (int u = 0; u < 2; u++) {
                const uint32_t w = u ? pw.y : pw.x;
                const uint32_t b0 = __byte_perm(w, 0u, sel0), b1 = __byte_perm(w, 0u, sel1);
                mma16816(acc[0], R0[u].x, R0[u].y, S0[u].x, S0[u].y, b0, b1);
                mma16816(acc[1], R0[u].z, R0[u].w, S0[u].z, S0[u].w, b0, b1);
                mma16816(acc[2], R1[u].x, R1[u].y, S1[u].x, S1[u].y, b0, b1);
                mma16816(acc[3], R1[u].z, R1[u].w, S1[u].z, S1[u].w, b0, b1);
            }
            __syncwarp();
            if (lane == 0 && LIVE()) mbar_arrive(bar_empty + slot * 8);
            advance();
        }
        float k8[8];
#pragma unroll
        for (int j = 0; j < 8; j++) {
            const float lo = acc[j >> 2][j & 3], hi = acc[2 + (j >> 2)][j & 3];
            const float send = (t & 1) ? lo : hi, keep = (t & 1) ? hi : lo;
            k8[j] = keep + __shfl_xor_sync(0xffffffffu, send, 9);
        }
        float k4[4];
#pragma unroll
        for (int j = 0; j < 4; j++) {
            const float send = (t & 2) ? k8[j] : k8[4 + j], keep = (t & 2) ? k8[4 + j] : k8[j];
            k4[j] = keep + __shfl_xor_sync(0xffffffffu, send, 18);
        }
        float* red = reinterpret_cast<float*>(smem + SM_RED) + cw * 128 + (t & 1) * 64 + c0 * 8 + (t >> 1) * 4;
        if (LIVE()) *reinterpret_cast<float4*>(red) = make_float4(k4[0], k4[1], k4[2], k4[3]);
        if (LIVE()) consumer_sync();
        if (ctid < 64) {
            const float* rd = reinterpret_cast<const float*>(smem + SM_RED) + ctid * 2;
            float s0 = 0.f, s1 = 0.f;
#pragma unroll
            for (int w = 0; w < NCW; w++) { const float2 v = *reinterpret_cast<const float2*>(rd + w * 128); s0 += v.x; s1 += v.y; }
            const uint32_t pk = pack_bf16(s0, s1);
            const uint32_t dst = sb + SM_OBF + r * 128 + (ctid & 31) * 4;
            const bool local = (ctid >> 5) == r;
            if (local && LIVE()) *reinterpret_cast<uint32_t*>(smem + SM_OBF + r * 128 + (ctid & 31) * 4) = pk;
            const uint32_t rdst = mapa(dst, r ^ 1), rbar = mapa(bar_o, r ^ 1);
            if (!local && LIVE()) st_async_b32(rdst, pk, rbar);
        }
        if (LIVE()) consumer_sync();
        if (LIVE()) mbar_wait_cluster(bar_o, 0);
    }

    {
        const uint32_t s0 = g >= 4 ? 0x4444u : ((g & 1) ? 0x1044u : 0x4410u);
        const uint32_t s1 = g >= 4 ? 0x4444u : ((g & 1) ? 0x3244u : 0x4432u);
        uint32_t bf[8][2];
#pragma unroll
        for (int u = 0; u < 8; u++) {
            const uint32_t w = *reinterpret_cast<const uint32_t*>(smem + SM_OBF + ((g >> 1) & 1) * 128 + (4 * u + t) * 4);
            bf[u][0] = __byte_perm(w, 0u, s0); bf[u][1] = __byte_perm(w, 0u, s1);
        }
        const int col = cw * 64 + g * 8;
        uint4* dst = g_part + ((size_t)(br * 64 + (t & 1) * 32 + (col >> 4)) * 64 + (blockIdx.x & 63)) * 4 + ((col >> 2) & 3);
        if (P.fused && LIVE()) mbar_wait(bar_z, 0);
        float acc[2][4];
#pragma unroll
        for (int j = 0; j < 2; j++) { acc[j][0] = acc[j][1] = acc[j][2] = acc[j][3] = 0.f; }
        const uint32_t tb = sb + SM_RING + (T_WO % NS) * TILE_BYTES + (2 * t) * WO_STRIDE + cw * 128 + g * 16;
#pragma unroll
        for (int j = 0; j < WO_TILES; j++) {
            if (LIVE()) mbar_wait(bar_full + (T_WO % NS + j) * 8, (T_WO / NS) & 1);
#pragma unroll
            for (int u = 0; u < 2; u++) {
                const uint4 R = lds128(tb + (16 * j + 8 * u) * WO_STRIDE);
                const uint4 S = lds128(tb + (16 * j + 8 * u + 1) * WO_STRIDE);
                mma16816(acc[0], R.x, R.y, S.x, S.y, bf[2 * j + u][0], bf[2 * j + u][1]);
                mma16816(acc[1], R.z, R.w, S.z, S.w, bf[2 * j + u][0], bf[2 * j + u][1]);
            }
        }
        if (t < 2 && LIVE()) {
            st_relaxed_v4(dst, make_uint4(nz_bits(acc[0][0]), nz_bits(acc[0][1]), nz_bits(acc[0][2]), nz_bits(acc[0][3])));
            st_relaxed_v4(dst + 1, make_uint4(nz_bits(acc[1][0]), nz_bits(acc[1][1]), nz_bits(acc[1][2]), nz_bits(acc[1][3])));
        }
    }
    if (P.fused) {
        unsigned dn = 0;
        if (tid == 0) asm volatile("atom.relaxed.gpu.global.add.u32 %0, [%1], 1;" : "=r"(dn) : "l"(&g_done) : "memory");
        const uint4* src = g_part + (size_t)blockIdx.x * 256 + cw * 32 + lane;
        const uint32_t fill = LIVE() ? 0u : 1u;
        uint4 v = make_uint4(fill, fill, fill, fill);
        unsigned n = 0;
        bool done;
        do {
            if (!all_nonzero(v)) v = ld_relaxed_v4(src);
            done = __all_sync(0xffffffffu, all_nonzero(v));
        } while (!done && ++n < SPIN_LIMIT);
        if (!done) __trap();
        __syncwarp();
        float s0 = __uint_as_float(v.x), s1 = __uint_as_float(v.y), s2 = __uint_as_float(v.z), s3 = __uint_as_float(v.w);
#pragma unroll
        for (int m = 4; m <= 16; m <<= 1) {
            s0 += __shfl_xor_sync(0xffffffffu, s0, m); s1 += __shfl_xor_sync(0xffffffffu, s1, m);
            s2 += __shfl_xor_sync(0xffffffffu, s2, m); s3 += __shfl_xor_sync(0xffffffffu, s3, m);
        }
        float* gsum = reinterpret_cast<float*>(smem + SM_GSUM);
        if (lane < 4 && LIVE()) *reinterpret_cast<float4*>(gsum + cw * 16 + lane * 4) = make_float4(s0, s1, s2, s3);
        if (LIVE()) consumer_sync();
        if (ctid < 8) {
            float t0 = 0.f, t1 = 0.f;
#pragma unroll
            for (int w = 0; w < NCW; w++) { const float2 x = *reinterpret_cast<const float2*>(gsum + w * 16 + ctid * 2); t0 += x.x; t1 += x.y; }
            const int cidx = blockIdx.x;
            if (LIVE())
                *reinterpret_cast<uint32_t*>(P.out + ((cidx >> 5) & 1) * 1024 + (cidx >> 6) * 512 + (cidx & 31) * 16 + ctid * 2) = pack_bf16(t0, t1);
        }
        if (tid == 0 && dn == 127u) { g_progress = 0u; g_zeroed = 0u; g_done = 0u; }
    }
    if (is_aux) {
        asm volatile("barrier.cluster.wait.acquire.aligned;" ::: "memory");
        if (lane == 0 && P.fused) {
            unsigned n = 0;
            while (!mbar_test(bar_g, 0) && ++n < SPIN_LIMIT) {
                unsigned gp;
                asm volatile("ld.relaxed.gpu.global.u32 %0, [%1];" : "=r"(gp) : "l"(&g_progress) : "memory");
                const int lim = (int)((gp + SLACK128) >> 7) + NF;
                if (lim > *reinterpret_cast<volatile int*>(smem + SM_LIMIT)) *reinterpret_cast<volatile int*>(smem + SM_LIMIT) = lim;
            }
        }
    }
}

__global__ void gather_kernel(__nv_bfloat16* out) {
    const int cidx = blockIdx.x, i = threadIdx.x;
    const float* src = reinterpret_cast<const float*>(g_part) + (size_t)cidx * 1024 + i;
    float tot = 0.f;
    for (int p = 0; p < 64; p++) tot += src[p * 16];
    out[((cidx >> 5) & 1) * 1024 + (cidx >> 6) * 512 + (cidx & 31) * 16 + i] = __float2bfloat16_rn(tot);
    if (cidx == 0 && i == 0) g_progress = 0u;
}

__global__ void __launch_bounds__(256) plain_attn_kernel(const __nv_bfloat16* x, const __nv_bfloat16* k, const __nv_bfloat16* v,
                                                         const __nv_bfloat16* wq, int br) {
    const int b = blockIdx.x >> 5, h = blockIdx.x & 31, tid = threadIdx.x;
    __shared__ float q[kDh], s[kW], red[256];
    if (tid < kDh) {
        float a = 0.f;
        for (int i = 0; i < kD; i++) a += __bfloat162float(x[b * kD + i]) * __bfloat162float(wq[(size_t)i * (kH * kDh) + h * kDh + tid]);
        q[tid] = bf16r(a);
    }
    __syncthreads();
    const __nv_bfloat16* kp = k + ((size_t)(b * kH + h) * kSk + (kSk - kW)) * kDh;
    const __nv_bfloat16* vp = v + ((size_t)(b * kH + h) * kSk + (kSk - kW)) * kDh;
    float mx = -INFINITY;
    for (int j = tid; j < kW; j += 256) {
        float a = 0.f;
        for (int d = 0; d < kDh; d++) a += q[d] * __bfloat162float(kp[(size_t)j * kDh + d]);
        a = bf16r(bf16r(a) * 0.08838834764831845f);
        s[j] = a; mx = fmaxf(mx, a);
    }
    red[tid] = mx; __syncthreads();
    for (int st = 128; st > 0; st >>= 1) { if (tid < st) red[tid] = fmaxf(red[tid], red[tid + st]); __syncthreads(); }
    mx = red[0]; __syncthreads();
    float sm = 0.f;
    for (int j = tid; j < kW; j += 256) { s[j] = expf(s[j] - mx); sm += s[j]; }
    red[tid] = sm; __syncthreads();
    for (int st = 128; st > 0; st >>= 1) { if (tid < st) red[tid] += red[tid + st]; __syncthreads(); }
    sm = red[0];
    for (int j = tid; j < kW; j += 256) s[j] = bf16r(s[j] / sm);
    __syncthreads();
    if (tid < kDh) {
        float a = 0.f;
        for (int j = 0; j < kW; j++) a += s[j] * __bfloat162float(vp[(size_t)j * kDh + tid]);
        g_o[(br * 2 + b) * (kH * kDh) + h * kDh + tid] = __float2bfloat16_rn(a);
    }
}
__global__ void __launch_bounds__(512) plain_out_kernel(const __nv_bfloat16* wo, __nv_bfloat16* out, int br) {
    const int b = blockIdx.x, n = threadIdx.x;
    float a = 0.f;
    for (int i = 0; i < kH * kDh; i++) a += __bfloat162float(g_o[(br * 2 + b) * (kH * kDh) + i]) * __bfloat162float(wo[(size_t)i * kD + n]);
    out[b * 1024 + br * 512 + n] = __float2bfloat16_rn(a);
}

}

typedef CUresult (*EncodeTiledFn)(CUtensorMap*, CUtensorMapDataType, cuuint32_t, void*, const cuuint64_t*, const cuuint64_t*,
                                  const cuuint32_t*, const cuuint32_t*, CUtensorMapInterleave, CUtensorMapSwizzle,
                                  CUtensorMapL2promotion, CUtensorMapFloatOOBfill);

extern "C" void kernel_launch(void* const* d_in, const int* in_sizes, int n_in, void* d_out, int out_size) {
    (void)in_sizes; (void)n_in; (void)out_size;
    static int fused = -1;
    static EncodeTiledFn encode = nullptr;
    if (fused < 0) {
        cudaFuncSetAttribute(attn_decode_kernel, cudaFuncAttributeMaxDynamicSharedMemorySize, SM_TOTAL);
        cudaLaunchConfig_t cfg = {};
        cfg.gridDim = dim3(128); cfg.blockDim = dim3(THREADS); cfg.dynamicSmemBytes = SM_TOTAL;
        cudaLaunchAttribute at[1];
        at[0].id = cudaLaunchAttributeClusterDimension;
        at[0].val.clusterDim.x = 2; at[0].val.clusterDim.y = 1; at[0].val.clusterDim.z = 1;
        cfg.attrs = at; cfg.numAttrs = 1;
        int nclusters = 0;
        cudaError_t e = cudaOccupancyMaxActiveClusters(&nclusters, attn_decode_kernel, &cfg);
        fused = (e == cudaSuccess && nclusters >= 64) ? 1 : 0;
        void* fn = nullptr;
        cudaDriverEntryPointQueryResult qres;
        if (cudaGetDriverEntryPoint("cuTensorMapEncodeTiled", &fn, cudaEnableDefault, &qres) == cudaSuccess &&
            qres == cudaDriverEntryPointSuccess)
            encode = (EncodeTiledFn)fn;
        (void)cudaGetLastError();
    }
    Params P;
    bool ok = encode != nullptr;
    for (int b = 0; b < 2 && ok; b++) {
        P.x[b] = (const __nv_bfloat16*)d_in[5 * b + 0];
        P.k[b] = (const __nv_bfloat16*)d_in[5 * b + 1];
        P.v[b] = (const __nv_bfloat16*)d_in[5 * b + 2];
        const cuuint32_t estr[2] = {1u, 1u};
        const cuuint64_t gdim[2] = {(cuuint64_t)(kH * kDh), (cuuint64_t)kD};
        const cuuint64_t gstride[1] = {(cuuint64_t)(kH * kDh * 2)};
        const cuuint32_t box[2] = {(cuuint32_t)kDh, 64u};
        ok = ok && encode(&P.tmq[b], CU_TENSOR_MAP_DATA_TYPE_BFLOAT16, 2, d_in[5 * b + 3], gdim, gstride, box, estr,
                          CU_TENSOR_MAP_INTERLEAVE_NONE, CU_TENSOR_MAP_SWIZZLE_NONE, CU_TENSOR_MAP_L2_PROMOTION_NONE,
                          CU_TENSOR_MAP_FLOAT_OOB_FILL_NONE) == CUDA_SUCCESS;
        const cuuint64_t odim[2] = {(cuuint64_t)(kD * 2 / 8), (cuuint64_t)(kH * kDh)};
        const cuuint64_t ostride[1] = {(cuuint64_t)(kD * 2)};
        const cuuint32_t obox[2] = {(cuuint32_t)(WO_STRIDE / 8), 16u};
        ok = ok && encode(&P.tmo[b], CU_TENSOR_MAP_DATA_TYPE_UINT64, 2, d_in[5 * b + 4], odim, ostride, obox, estr,
                          CU_TENSOR_MAP_INTERLEAVE_NONE, CU_TENSOR_MAP_SWIZZLE_NONE, CU_TENSOR_MAP_L2_PROMOTION_NONE,
                          CU_TENSOR_MAP_FLOAT_OOB_FILL_NONE) == CUDA_SUCCESS;
    }
    if (!ok) {
        for (int b = 0; b < 2; b++) {
            plain_attn_kernel<<<64, 256>>>((const __nv_bfloat16*)d_in[5 * b + 0], (const __nv_bfloat16*)d_in[5 * b + 1],
                                           (const __nv_bfloat16*)d_in[5 * b + 2], (const __nv_bfloat16*)d_in[5 * b + 3], b);
            plain_out_kernel<<<2, 512>>>((const __nv_bfloat16*)d_in[5 * b + 4], (__nv_bfloat16*)d_out, b);
        }
        return;
    }
    P.out = (__nv_bfloat16*)d_out;
    P.fused = fused;
    attn_decode_kernel<<<128, THREADS, SM_TOTAL>>>(P);
    if (!fused) gather_kernel<<<128, 16>>>(P.out);
}
```
